```python
import torch

def _softmax(x, axis=-1):
    return torch.softmax(x, dim=axis)
def _gelu(x):
    return torch.nn.functional.gelu(x, approximate="tanh")
def _silu(x):
    return torch.nn.functional.silu(x)
def _sigmoid(x):
    return torch.sigmoid(x)
def _layernorm(x, axis=-1, eps=1e-5):
    m = x.mean(dim=axis, keepdim=True)
    v = x.var(dim=axis, keepdim=True, unbiased=False)
    return (x - m) / torch.sqrt(v + eps)
def _scatter_add(tgt, idx, src, axis=0):
    return tgt.clone().index_add_(axis, idx, src)
def _segment_sum(src, seg, n):
    out = torch.zeros((n,) + src.shape[1:], dtype=src.dtype)
    return out.index_add_(0, seg, src)
def _pad(x, pw):
    flat = tuple(v for pair in reversed(pw) for v in pair)
    return torch.nn.functional.pad(x, flat)

kernel_name = 'sequential_preLN__sliding_block__dense_activation_silu__prompt'

def setup_inputs():

    _w = (lambda a: (lambda t: t.to(torch.bfloat16) if t.is_floating_point() else t)(torch.as_tensor(a)))
    def _A_setup():
        B, S, D = 1, 2048, 640
        return {
            "x": _w((lambda *s: torch.randn(*s, dtype=torch.bfloat16) * 0.05)(B, S, D)),
            "wqkv": _w((lambda *s: torch.randn(*s, dtype=torch.bfloat16) * 0.05)(D, 3 * D)),
            "wo": _w((lambda *s: torch.randn(*s, dtype=torch.bfloat16) * 0.05)(D, D)),
        }
    _A_in = _A_setup()

    def _B_setup():
        B, S, D, F = 1, 2048, 640, 1728
        return {
            "x": _w((lambda *s: torch.randn(*s, dtype=torch.bfloat16) * 0.05)(B, S, D)),
            "w1": _w((lambda *s: torch.randn(*s, dtype=torch.bfloat16) * 3.2)(D, F) * (D ** -0.5)),
            "w2": _w((lambda *s: torch.randn(*s, dtype=torch.bfloat16) * 0.4)(F, D) * (F ** -0.5)),
        }
    _B_in = _B_setup()

    return {
        "A_x": _A_in["x"],
        "A_wqkv": _A_in["wqkv"],
        "A_wo": _A_in["wo"],
        "B_x": _B_in["x"],
        "B_w1": _B_in["w1"],
        "B_w2": _B_in["w2"],
    }

def reference(A_x, A_wqkv, A_wo, B_x, B_w1, B_w2):
    def _A_ref(x, wqkv, wo):
        B, S, D = x.shape
        H = 32; Dh = D // H; W = 256
        qkv = (lambda x, *d: x.permute(*d))((x @ wqkv).reshape(B, S, 3, H, Dh), 2, 0, 3, 1, 4)
        q, k, v = qkv[0], qkv[1], qkv[2]
        scores = torch.einsum("bhqd,bhkd->bhqk", q, k) * (Dh ** -0.5)
        idx = torch.arange(S)
        mask = (idx[:, None] - idx[None, :] >= 0) & (idx[:, None] - idx[None, :] < W)
        scores = torch.where(mask[None, None], scores, -1e9)
        p = _softmax(scores, axis=-1)
        o = torch.einsum("bhqk,bhkd->bhqd", p, v)
        return (lambda x, *d: x.permute(*d))(o, 0, 2, 1, 3).reshape(B, S, D) @ wo

    def _B_ref(x, w1, w2):
        h = torch.einsum("bsd,df->bsf", x, w1)
        h = _silu(h)
        out = torch.einsum("bsf,fd->bsd", h, w2)
        return out

    x = A_x
    h = x + _A_ref(_layernorm(x, axis=-1), A_wqkv, A_wo)
    h2 = h + _B_ref(_layernorm(h, axis=-1), B_w1, B_w2)
    return h2
```

```cpp
#include <cuda_runtime.h>
#include <cuda.h>
#include <cuda_bf16.h>
#include <stdint.h>
#include <limits.h>

#define DEVI __device__ __forceinline__

template<int TB> __device__ __forceinline__ void wgmma_ss_n64(float* d, uint64_t da, uint64_t db, int sd) {
  asm volatile("{.reg .pred p; setp.ne.b32 p, %34, 0;\n"
  "wgmma.mma_async.sync.aligned.m64n64k16.f32.bf16.bf16 {%0, %1, %2, %3, %4, %5, %6, %7, %8, %9, %10, %11, %12, %13, %14, %15, %16, %17, %18, %19, %20, %21, %22, %23, %24, %25, %26, %27, %28, %29, %30, %31}, %32, %33, p, 1, 1, 0, %35;}"
  : "+f"(d[0]), "+f"(d[1]), "+f"(d[2]), "+f"(d[3]), "+f"(d[4]), "+f"(d[5]), "+f"(d[6]), "+f"(d[7]), "+f"(d[8]), "+f"(d[9]), "+f"(d[10]), "+f"(d[11]), "+f"(d[12]), "+f"(d[13]), "+f"(d[14]), "+f"(d[15]), "+f"(d[16]), "+f"(d[17]), "+f"(d[18]), "+f"(d[19]), "+f"(d[20]), "+f"(d[21]), "+f"(d[22]), "+f"(d[23]), "+f"(d[24]), "+f"(d[25]), "+f"(d[26]), "+f"(d[27]), "+f"(d[28]), "+f"(d[29]), "+f"(d[30]), "+f"(d[31])
  : "l"(da), "l"(db), "r"(sd), "n"(TB));
}
template<int TB> __device__ __forceinline__ void wgmma_ss_n96(float* d, uint64_t da, uint64_t db, int sd) {
  asm volatile("{.reg .pred p; setp.ne.b32 p, %50, 0;\n"
  "wgmma.mma_async.sync.aligned.m64n96k16.f32.bf16.bf16 {%0, %1, %2, %3, %4, %5, %6, %7, %8, %9, %10, %11, %12, %13, %14, %15, %16, %17, %18, %19, %20, %21, %22, %23, %24, %25, %26, %27, %28, %29, %30, %31, %32, %33, %34, %35, %36, %37, %38, %39, %40, %41, %42, %43, %44, %45, %46, %47}, %48, %49, p, 1, 1, 0, %51;}"
  : "+f"(d[0]), "+f"(d[1]), "+f"(d[2]), "+f"(d[3]), "+f"(d[4]), "+f"(d[5]), "+f"(d[6]), "+f"(d[7]), "+f"(d[8]), "+f"(d[9]), "+f"(d[10]), "+f"(d[11]), "+f"(d[12]), "+f"(d[13]), "+f"(d[14]), "+f"(d[15]), "+f"(d[16]), "+f"(d[17]), "+f"(d[18]), "+f"(d[19]), "+f"(d[20]), "+f"(d[21]), "+f"(d[22]), "+f"(d[23]), "+f"(d[24]), "+f"(d[25]), "+f"(d[26]), "+f"(d[27]), "+f"(d[28]), "+f"(d[29]), "+f"(d[30]), "+f"(d[31]), "+f"(d[32]), "+f"(d[33]), "+f"(d[34]), "+f"(d[35]), "+f"(d[36]), "+f"(d[37]), "+f"(d[38]), "+f"(d[39]), "+f"(d[40]), "+f"(d[41]), "+f"(d[42]), "+f"(d[43]), "+f"(d[44]), "+f"(d[45]), "+f"(d[46]), "+f"(d[47])
  : "l"(da), "l"(db), "r"(sd), "n"(TB));
}
template<int TB> __device__ __forceinline__ void wgmma_rs_n24(float* d, const uint32_t* a, uint64_t db, int sd) {
  asm volatile("{.reg .pred p; setp.ne.b32 p, %17, 0;\n"
  "wgmma.mma_async.sync.aligned.m64n24k16.f32.bf16.bf16 {%0, %1, %2, %3, %4, %5, %6, %7, %8, %9, %10, %11}, {%12,%13,%14,%15}, %16, p, 1, 1, %18;}"
  : "+f"(d[0]), "+f"(d[1]), "+f"(d[2]), "+f"(d[3]), "+f"(d[4]), "+f"(d[5]), "+f"(d[6]), "+f"(d[7]), "+f"(d[8]), "+f"(d[9]), "+f"(d[10]), "+f"(d[11])
  : "r"(a[0]), "r"(a[1]), "r"(a[2]), "r"(a[3]), "l"(db), "r"(sd), "n"(TB));
}
template<int TB> __device__ __forceinline__ void wgmma_rs_n48(float* d, const uint32_t* a, uint64_t db, int sd) {
  asm volatile("{.reg .pred p; setp.ne.b32 p, %29, 0;\n"
  "wgmma.mma_async.sync.aligned.m64n48k16.f32.bf16.bf16 {%0, %1, %2, %3, %4, %5, %6, %7, %8, %9, %10, %11, %12, %13, %14, %15, %16, %17, %18, %19, %20, %21, %22, %23}, {%24,%25,%26,%27}, %28, p, 1, 1, %30;}"
  : "+f"(d[0]), "+f"(d[1]), "+f"(d[2]), "+f"(d[3]), "+f"(d[4]), "+f"(d[5]), "+f"(d[6]), "+f"(d[7]), "+f"(d[8]), "+f"(d[9]), "+f"(d[10]), "+f"(d[11]), "+f"(d[12]), "+f"(d[13]), "+f"(d[14]), "+f"(d[15]), "+f"(d[16]), "+f"(d[17]), "+f"(d[18]), "+f"(d[19]), "+f"(d[20]), "+f"(d[21]), "+f"(d[22]), "+f"(d[23])
  : "r"(a[0]), "r"(a[1]), "r"(a[2]), "r"(a[3]), "l"(db), "r"(sd), "n"(TB));
}
template<int TB> __device__ __forceinline__ void wgmma_rs_n64(float* d, const uint32_t* a, uint64_t db, int sd) {
  asm volatile("{.reg .pred p; setp.ne.b32 p, %37, 0;\n"
  "wgmma.mma_async.sync.aligned.m64n64k16.f32.bf16.bf16 {%0, %1, %2, %3, %4, %5, %6, %7, %8, %9, %10, %11, %12, %13, %14, %15, %16, %17, %18, %19, %20, %21, %22, %23, %24, %25, %26, %27, %28, %29, %30, %31}, {%32,%33,%34,%35}, %36, p, 1, 1, %38;}"
  : "+f"(d[0]), "+f"(d[1]), "+f"(d[2]), "+f"(d[3]), "+f"(d[4]), "+f"(d[5]), "+f"(d[6]), "+f"(d[7]), "+f"(d[8]), "+f"(d[9]), "+f"(d[10]), "+f"(d[11]), "+f"(d[12]), "+f"(d[13]), "+f"(d[14]), "+f"(d[15]), "+f"(d[16]), "+f"(d[17]), "+f"(d[18]), "+f"(d[19]), "+f"(d[20]), "+f"(d[21]), "+f"(d[22]), "+f"(d[23]), "+f"(d[24]), "+f"(d[25]), "+f"(d[26]), "+f"(d[27]), "+f"(d[28]), "+f"(d[29]), "+f"(d[30]), "+f"(d[31])
  : "r"(a[0]), "r"(a[1]), "r"(a[2]), "r"(a[3]), "l"(db), "r"(sd), "n"(TB));
}
template<int TB> __device__ __forceinline__ void wgmma_rs_n80(float* d, const uint32_t* a, uint64_t db, int sd) {
  asm volatile("{.reg .pred p; setp.ne.b32 p, %45, 0;\n"
  "wgmma.mma_async.sync.aligned.m64n80k16.f32.bf16.bf16 {%0, %1, %2, %3, %4, %5, %6, %7, %8, %9, %10, %11, %12, %13, %14, %15, %16, %17, %18, %19, %20, %21, %22, %23, %24, %25, %26, %27, %28, %29, %30, %31, %32, %33, %34, %35, %36, %37, %38, %39}, {%40,%41,%42,%43}, %44, p, 1, 1, %46;}"
  : "+f"(d[0]), "+f"(d[1]), "+f"(d[2]), "+f"(d[3]), "+f"(d[4]), "+f"(d[5]), "+f"(d[6]), "+f"(d[7]), "+f"(d[8]), "+f"(d[9]), "+f"(d[10]), "+f"(d[11]), "+f"(d[12]), "+f"(d[13]), "+f"(d[14]), "+f"(d[15]), "+f"(d[16]), "+f"(d[17]), "+f"(d[18]), "+f"(d[19]), "+f"(d[20]), "+f"(d[21]), "+f"(d[22]), "+f"(d[23]), "+f"(d[24]), "+f"(d[25]), "+f"(d[26]), "+f"(d[27]), "+f"(d[28]), "+f"(d[29]), "+f"(d[30]), "+f"(d[31]), "+f"(d[32]), "+f"(d[33]), "+f"(d[34]), "+f"(d[35]), "+f"(d[36]), "+f"(d[37]), "+f"(d[38]), "+f"(d[39])
  : "r"(a[0]), "r"(a[1]), "r"(a[2]), "r"(a[3]), "l"(db), "r"(sd), "n"(TB));
}
template<int TB> __device__ __forceinline__ void wgmma_rs_n96(float* d, const uint32_t* a, uint64_t db, int sd) {
  asm volatile("{.reg .pred p; setp.ne.b32 p, %53, 0;\n"
  "wgmma.mma_async.sync.aligned.m64n96k16.f32.bf16.bf16 {%0, %1, %2, %3, %4, %5, %6, %7, %8, %9, %10, %11, %12, %13, %14, %15, %16, %17, %18, %19, %20, %21, %22, %23, %24, %25, %26, %27, %28, %29, %30, %31, %32, %33, %34, %35, %36, %37, %38, %39, %40, %41, %42, %43, %44, %45, %46, %47}, {%48,%49,%50,%51}, %52, p, 1, 1, %54;}"
  : "+f"(d[0]), "+f"(d[1]), "+f"(d[2]), "+f"(d[3]), "+f"(d[4]), "+f"(d[5]), "+f"(d[6]), "+f"(d[7]), "+f"(d[8]), "+f"(d[9]), "+f"(d[10]), "+f"(d[11]), "+f"(d[12]), "+f"(d[13]), "+f"(d[14]), "+f"(d[15]), "+f"(d[16]), "+f"(d[17]), "+f"(d[18]), "+f"(d[19]), "+f"(d[20]), "+f"(d[21]), "+f"(d[22]), "+f"(d[23]), "+f"(d[24]), "+f"(d[25]), "+f"(d[26]), "+f"(d[27]), "+f"(d[28]), "+f"(d[29]), "+f"(d[30]), "+f"(d[31]), "+f"(d[32]), "+f"(d[33]), "+f"(d[34]), "+f"(d[35]), "+f"(d[36]), "+f"(d[37]), "+f"(d[38]), "+f"(d[39]), "+f"(d[40]), "+f"(d[41]), "+f"(d[42]), "+f"(d[43]), "+f"(d[44]), "+f"(d[45]), "+f"(d[46]), "+f"(d[47])
  : "r"(a[0]), "r"(a[1]), "r"(a[2]), "r"(a[3]), "l"(db), "r"(sd), "n"(TB));
}
template<int TB> __device__ __forceinline__ void wgmma_rs_n128(float* d, const uint32_t* a, uint64_t db, int sd) {
  asm volatile("{.reg .pred p; setp.ne.b32 p, %69, 0;\n"
  "wgmma.mma_async.sync.aligned.m64n128k16.f32.bf16.bf16 {%0, %1, %2, %3, %4, %5, %6, %7, %8, %9, %10, %11, %12, %13, %14, %15, %16, %17, %18, %19, %20, %21, %22, %23, %24, %25, %26, %27, %28, %29, %30, %31, %32, %33, %34, %35, %36, %37, %38, %39, %40, %41, %42, %43, %44, %45, %46, %47, %48, %49, %50, %51, %52, %53, %54, %55, %56, %57, %58, %59, %60, %61, %62, %63}, {%64,%65,%66,%67}, %68, p, 1, 1, %70;}"
  : "+f"(d[0]), "+f"(d[1]), "+f"(d[2]), "+f"(d[3]), "+f"(d[4]), "+f"(d[5]), "+f"(d[6]), "+f"(d[7]), "+f"(d[8]), "+f"(d[9]), "+f"(d[10]), "+f"(d[11]), "+f"(d[12]), "+f"(d[13]), "+f"(d[14]), "+f"(d[15]), "+f"(d[16]), "+f"(d[17]), "+f"(d[18]), "+f"(d[19]), "+f"(d[20]), "+f"(d[21]), "+f"(d[22]), "+f"(d[23]), "+f"(d[24]), "+f"(d[25]), "+f"(d[26]), "+f"(d[27]), "+f"(d[28]), "+f"(d[29]), "+f"(d[30]), "+f"(d[31]), "+f"(d[32]), "+f"(d[33]), "+f"(d[34]), "+f"(d[35]), "+f"(d[36]), "+f"(d[37]), "+f"(d[38]), "+f"(d[39]), "+f"(d[40]), "+f"(d[41]), "+f"(d[42]), "+f"(d[43]), "+f"(d[44]), "+f"(d[45]), "+f"(d[46]), "+f"(d[47]), "+f"(d[48]), "+f"(d[49]), "+f"(d[50]), "+f"(d[51]), "+f"(d[52]), "+f"(d[53]), "+f"(d[54]), "+f"(d[55]), "+f"(d[56]), "+f"(d[57]), "+f"(d[58]), "+f"(d[59]), "+f"(d[60]), "+f"(d[61]), "+f"(d[62]), "+f"(d[63])
  : "r"(a[0]), "r"(a[1]), "r"(a[2]), "r"(a[3]), "l"(db), "r"(sd), "n"(TB));
}
template<int TB> __device__ __forceinline__ void wgmma_rs_n160(float* d, const uint32_t* a, uint64_t db, int sd) {
  asm volatile("{.reg .pred p; setp.ne.b32 p, %85, 0;\n"
  "wgmma.mma_async.sync.aligned.m64n160k16.f32.bf16.bf16 {%0, %1, %2, %3, %4, %5, %6, %7, %8, %9, %10, %11, %12, %13, %14, %15, %16, %17, %18, %19, %20, %21, %22, %23, %24, %25, %26, %27, %28, %29, %30, %31, %32, %33, %34, %35, %36, %37, %38, %39, %40, %41, %42, %43, %44, %45, %46, %47, %48, %49, %50, %51, %52, %53, %54, %55, %56, %57, %58, %59, %60, %61, %62, %63, %64, %65, %66, %67, %68, %69, %70, %71, %72, %73, %74, %75, %76, %77, %78, %79}, {%80,%81,%82,%83}, %84, p, 1, 1, %86;}"
  : "+f"(d[0]), "+f"(d[1]), "+f"(d[2]), "+f"(d[3]), "+f"(d[4]), "+f"(d[5]), "+f"(d[6]), "+f"(d[7]), "+f"(d[8]), "+f"(d[9]), "+f"(d[10]), "+f"(d[11]), "+f"(d[12]), "+f"(d[13]), "+f"(d[14]), "+f"(d[15]), "+f"(d[16]), "+f"(d[17]), "+f"(d[18]), "+f"(d[19]), "+f"(d[20]), "+f"(d[21]), "+f"(d[22]), "+f"(d[23]), "+f"(d[24]), "+f"(d[25]), "+f"(d[26]), "+f"(d[27]), "+f"(d[28]), "+f"(d[29]), "+f"(d[30]), "+f"(d[31]), "+f"(d[32]), "+f"(d[33]), "+f"(d[34]), "+f"(d[35]), "+f"(d[36]), "+f"(d[37]), "+f"(d[38]), "+f"(d[39]), "+f"(d[40]), "+f"(d[41]), "+f"(d[42]), "+f"(d[43]), "+f"(d[44]), "+f"(d[45]), "+f"(d[46]), "+f"(d[47]), "+f"(d[48]), "+f"(d[49]), "+f"(d[50]), "+f"(d[51]), "+f"(d[52]), "+f"(d[53]), "+f"(d[54]), "+f"(d[55]), "+f"(d[56]), "+f"(d[57]), "+f"(d[58]), "+f"(d[59]), "+f"(d[60]), "+f"(d[61]), "+f"(d[62]), "+f"(d[63]), "+f"(d[64]), "+f"(d[65]), "+f"(d[66]), "+f"(d[67]), "+f"(d[68]), "+f"(d[69]), "+f"(d[70]), "+f"(d[71]), "+f"(d[72]), "+f"(d[73]), "+f"(d[74]), "+f"(d[75]), "+f"(d[76]), "+f"(d[77]), "+f"(d[78]), "+f"(d[79])
  : "r"(a[0]), "r"(a[1]), "r"(a[2]), "r"(a[3]), "l"(db), "r"(sd), "n"(TB));
}
template<int TB> __device__ __forceinline__ void wgmma_rs_n192(float* d, const uint32_t* a, uint64_t db, int sd) {
  asm volatile("{.reg .pred p; setp.ne.b32 p, %101, 0;\n"
  "wgmma.mma_async.sync.aligned.m64n192k16.f32.bf16.bf16 {%0, %1, %2, %3, %4, %5, %6, %7, %8, %9, %10, %11, %12, %13, %14, %15, %16, %17, %18, %19, %20, %21, %22, %23, %24, %25, %26, %27, %28, %29, %30, %31, %32, %33, %34, %35, %36, %37, %38, %39, %40, %41, %42, %43, %44, %45, %46, %47, %48, %49, %50, %51, %52, %53, %54, %55, %56, %57, %58, %59, %60, %61, %62, %63, %64, %65, %66, %67, %68, %69, %70, %71, %72, %73, %74, %75, %76, %77, %78, %79, %80, %81, %82, %83, %84, %85, %86, %87, %88, %89, %90, %91, %92, %93, %94, %95}, {%96,%97,%98,%99}, %100, p, 1, 1, %102;}"
  : "+f"(d[0]), "+f"(d[1]), "+f"(d[2]), "+f"(d[3]), "+f"(d[4]), "+f"(d[5]), "+f"(d[6]), "+f"(d[7]), "+f"(d[8]), "+f"(d[9]), "+f"(d[10]), "+f"(d[11]), "+f"(d[12]), "+f"(d[13]), "+f"(d[14]), "+f"(d[15]), "+f"(d[16]), "+f"(d[17]), "+f"(d[18]), "+f"(d[19]), "+f"(d[20]), "+f"(d[21]), "+f"(d[22]), "+f"(d[23]), "+f"(d[24]), "+f"(d[25]), "+f"(d[26]), "+f"(d[27]), "+f"(d[28]), "+f"(d[29]), "+f"(d[30]), "+f"(d[31]), "+f"(d[32]), "+f"(d[33]), "+f"(d[34]), "+f"(d[35]), "+f"(d[36]), "+f"(d[37]), "+f"(d[38]), "+f"(d[39]), "+f"(d[40]), "+f"(d[41]), "+f"(d[42]), "+f"(d[43]), "+f"(d[44]), "+f"(d[45]), "+f"(d[46]), "+f"(d[47]), "+f"(d[48]), "+f"(d[49]), "+f"(d[50]), "+f"(d[51]), "+f"(d[52]), "+f"(d[53]), "+f"(d[54]), "+f"(d[55]), "+f"(d[56]), "+f"(d[57]), "+f"(d[58]), "+f"(d[59]), "+f"(d[60]), "+f"(d[61]), "+f"(d[62]), "+f"(d[63]), "+f"(d[64]), "+f"(d[65]), "+f"(d[66]), "+f"(d[67]), "+f"(d[68]), "+f"(d[69]), "+f"(d[70]), "+f"(d[71]), "+f"(d[72]), "+f"(d[73]), "+f"(d[74]), "+f"(d[75]), "+f"(d[76]), "+f"(d[77]), "+f"(d[78]), "+f"(d[79]), "+f"(d[80]), "+f"(d[81]), "+f"(d[82]), "+f"(d[83]), "+f"(d[84]), "+f"(d[85]), "+f"(d[86]), "+f"(d[87]), "+f"(d[88]), "+f"(d[89]), "+f"(d[90]), "+f"(d[91]), "+f"(d[92]), "+f"(d[93]), "+f"(d[94]), "+f"(d[95])
  : "r"(a[0]), "r"(a[1]), "r"(a[2]), "r"(a[3]), "l"(db), "r"(sd), "n"(TB));
}
template<int TB> __device__ __forceinline__ void wgmma_rs_n224(float* d, const uint32_t* a, uint64_t db, int sd) {
  asm volatile("{.reg .pred p; setp.ne.b32 p, %117, 0;\n"
  "wgmma.mma_async.sync.aligned.m64n224k16.f32.bf16.bf16 {%0, %1, %2, %3, %4, %5, %6, %7, %8, %9, %10, %11, %12, %13, %14, %15, %16, %17, %18, %19, %20, %21, %22, %23, %24, %25, %26, %27, %28, %29, %30, %31, %32, %33, %34, %35, %36, %37, %38, %39, %40, %41, %42, %43, %44, %45, %46, %47, %48, %49, %50, %51, %52, %53, %54, %55, %56, %57, %58, %59, %60, %61, %62, %63, %64, %65, %66, %67, %68, %69, %70, %71, %72, %73, %74, %75, %76, %77, %78, %79, %80, %81, %82, %83, %84, %85, %86, %87, %88, %89, %90, %91, %92, %93, %94, %95, %96, %97, %98, %99, %100, %101, %102, %103, %104, %105, %106, %107, %108, %109, %110, %111}, {%112,%113,%114,%115}, %116, p, 1, 1, %118;}"
  : "+f"(d[0]), "+f"(d[1]), "+f"(d[2]), "+f"(d[3]), "+f"(d[4]), "+f"(d[5]), "+f"(d[6]), "+f"(d[7]), "+f"(d[8]), "+f"(d[9]), "+f"(d[10]), "+f"(d[11]), "+f"(d[12]), "+f"(d[13]), "+f"(d[14]), "+f"(d[15]), "+f"(d[16]), "+f"(d[17]), "+f"(d[18]), "+f"(d[19]), "+f"(d[20]), "+f"(d[21]), "+f"(d[22]), "+f"(d[23]), "+f"(d[24]), "+f"(d[25]), "+f"(d[26]), "+f"(d[27]), "+f"(d[28]), "+f"(d[29]), "+f"(d[30]), "+f"(d[31]), "+f"(d[32]), "+f"(d[33]), "+f"(d[34]), "+f"(d[35]), "+f"(d[36]), "+f"(d[37]), "+f"(d[38]), "+f"(d[39]), "+f"(d[40]), "+f"(d[41]), "+f"(d[42]), "+f"(d[43]), "+f"(d[44]), "+f"(d[45]), "+f"(d[46]), "+f"(d[47]), "+f"(d[48]), "+f"(d[49]), "+f"(d[50]), "+f"(d[51]), "+f"(d[52]), "+f"(d[53]), "+f"(d[54]), "+f"(d[55]), "+f"(d[56]), "+f"(d[57]), "+f"(d[58]), "+f"(d[59]), "+f"(d[60]), "+f"(d[61]), "+f"(d[62]), "+f"(d[63]), "+f"(d[64]), "+f"(d[65]), "+f"(d[66]), "+f"(d[67]), "+f"(d[68]), "+f"(d[69]), "+f"(d[70]), "+f"(d[71]), "+f"(d[72]), "+f"(d[73]), "+f"(d[74]), "+f"(d[75]), "+f"(d[76]), "+f"(d[77]), "+f"(d[78]), "+f"(d[79]), "+f"(d[80]), "+f"(d[81]), "+f"(d[82]), "+f"(d[83]), "+f"(d[84]), "+f"(d[85]), "+f"(d[86]), "+f"(d[87]), "+f"(d[88]), "+f"(d[89]), "+f"(d[90]), "+f"(d[91]), "+f"(d[92]), "+f"(d[93]), "+f"(d[94]), "+f"(d[95]), "+f"(d[96]), "+f"(d[97]), "+f"(d[98]), "+f"(d[99]), "+f"(d[100]), "+f"(d[101]), "+f"(d[102]), "+f"(d[103]), "+f"(d[104]), "+f"(d[105]), "+f"(d[106]), "+f"(d[107]), "+f"(d[108]), "+f"(d[109]), "+f"(d[110]), "+f"(d[111])
  : "r"(a[0]), "r"(a[1]), "r"(a[2]), "r"(a[3]), "l"(db), "r"(sd), "n"(TB));
}
template<int TB> __device__ __forceinline__ void wgmma_rp_n160(float* d, const uint32_t* a, uint64_t db, int on) {
  asm volatile("{.reg .pred p, q; setp.ne.b32 p, 1, 0; setp.ne.b32 q, %85, 0;\n"
  "@q wgmma.mma_async.sync.aligned.m64n160k16.f32.bf16.bf16 {%0, %1, %2, %3, %4, %5, %6, %7, %8, %9, %10, %11, %12, %13, %14, %15, %16, %17, %18, %19, %20, %21, %22, %23, %24, %25, %26, %27, %28, %29, %30, %31, %32, %33, %34, %35, %36, %37, %38, %39, %40, %41, %42, %43, %44, %45, %46, %47, %48, %49, %50, %51, %52, %53, %54, %55, %56, %57, %58, %59, %60, %61, %62, %63, %64, %65, %66, %67, %68, %69, %70, %71, %72, %73, %74, %75, %76, %77, %78, %79}, {%80,%81,%82,%83}, %84, p, 1, 1, %86;}"
  : "+f"(d[0]), "+f"(d[1]), "+f"(d[2]), "+f"(d[3]), "+f"(d[4]), "+f"(d[5]), "+f"(d[6]), "+f"(d[7]), "+f"(d[8]), "+f"(d[9]), "+f"(d[10]), "+f"(d[11]), "+f"(d[12]), "+f"(d[13]), "+f"(d[14]), "+f"(d[15]), "+f"(d[16]), "+f"(d[17]), "+f"(d[18]), "+f"(d[19]), "+f"(d[20]), "+f"(d[21]), "+f"(d[22]), "+f"(d[23]), "+f"(d[24]), "+f"(d[25]), "+f"(d[26]), "+f"(d[27]), "+f"(d[28]), "+f"(d[29]), "+f"(d[30]), "+f"(d[31]), "+f"(d[32]), "+f"(d[33]), "+f"(d[34]), "+f"(d[35]), "+f"(d[36]), "+f"(d[37]), "+f"(d[38]), "+f"(d[39]), "+f"(d[40]), "+f"(d[41]), "+f"(d[42]), "+f"(d[43]), "+f"(d[44]), "+f"(d[45]), "+f"(d[46]), "+f"(d[47]), "+f"(d[48]), "+f"(d[49]), "+f"(d[50]), "+f"(d[51]), "+f"(d[52]), "+f"(d[53]), "+f"(d[54]), "+f"(d[55]), "+f"(d[56]), "+f"(d[57]), "+f"(d[58]), "+f"(d[59]), "+f"(d[60]), "+f"(d[61]), "+f"(d[62]), "+f"(d[63]), "+f"(d[64]), "+f"(d[65]), "+f"(d[66]), "+f"(d[67]), "+f"(d[68]), "+f"(d[69]), "+f"(d[70]), "+f"(d[71]), "+f"(d[72]), "+f"(d[73]), "+f"(d[74]), "+f"(d[75]), "+f"(d[76]), "+f"(d[77]), "+f"(d[78]), "+f"(d[79])
  : "r"(a[0]), "r"(a[1]), "r"(a[2]), "r"(a[3]), "l"(db), "r"(on), "n"(TB));
}
template<int TB> __device__ __forceinline__ void wgmma_rz_n8(float* d, const uint32_t* a, uint64_t db) {
  asm volatile("{.reg .pred p; setp.ne.b32 p, 0, 0;\n"
  "wgmma.mma_async.sync.aligned.m64n8k16.f32.bf16.bf16 {%0, %1, %2, %3}, {%4,%5,%6,%7}, %8, p, 1, 1, %9;}"
  : "=f"(d[0]), "=f"(d[1]), "=f"(d[2]), "=f"(d[3])
  : "r"(a[0]), "r"(a[1]), "r"(a[2]), "r"(a[3]), "l"(db), "n"(TB));
}
template<int TB> __device__ __forceinline__ void wgmma_rz_n24(float* d, const uint32_t* a, uint64_t db) {
  asm volatile("{.reg .pred p; setp.ne.b32 p, 0, 0;\n"
  "wgmma.mma_async.sync.aligned.m64n24k16.f32.bf16.bf16 {%0, %1, %2, %3, %4, %5, %6, %7, %8, %9, %10, %11}, {%12,%13,%14,%15}, %16, p, 1, 1, %17;}"
  : "=f"(d[0]), "=f"(d[1]), "=f"(d[2]), "=f"(d[3]), "=f"(d[4]), "=f"(d[5]), "=f"(d[6]), "=f"(d[7]), "=f"(d[8]), "=f"(d[9]), "=f"(d[10]), "=f"(d[11])
  : "r"(a[0]), "r"(a[1]), "r"(a[2]), "r"(a[3]), "l"(db), "n"(TB));
}
template<int TB> __device__ __forceinline__ void wgmma_sz_n64(float* d, uint64_t da, uint64_t db) {
  asm volatile("{.reg .pred p; setp.ne.b32 p, 0, 0;\n"
  "wgmma.mma_async.sync.aligned.m64n64k16.f32.bf16.bf16 {%0, %1, %2, %3, %4, %5, %6, %7, %8, %9, %10, %11, %12, %13, %14, %15, %16, %17, %18, %19, %20, %21, %22, %23, %24, %25, %26, %27, %28, %29, %30, %31}, %32, %33, p, 1, 1, 0, %34;}"
  : "=f"(d[0]), "=f"(d[1]), "=f"(d[2]), "=f"(d[3]), "=f"(d[4]), "=f"(d[5]), "=f"(d[6]), "=f"(d[7]), "=f"(d[8]), "=f"(d[9]), "=f"(d[10]), "=f"(d[11]), "=f"(d[12]), "=f"(d[13]), "=f"(d[14]), "=f"(d[15]), "=f"(d[16]), "=f"(d[17]), "=f"(d[18]), "=f"(d[19]), "=f"(d[20]), "=f"(d[21]), "=f"(d[22]), "=f"(d[23]), "=f"(d[24]), "=f"(d[25]), "=f"(d[26]), "=f"(d[27]), "=f"(d[28]), "=f"(d[29]), "=f"(d[30]), "=f"(d[31])
  : "l"(da), "l"(db), "n"(TB));
}
template<int N,int TB> __device__ __forceinline__ void wg_ss(float* d, uint64_t da, uint64_t db, int sd){
  if constexpr (N==64) wgmma_ss_n64<TB>(d,da,db,sd);
  if constexpr (N==96) wgmma_ss_n96<TB>(d,da,db,sd);
}
template<int N,int TB> __device__ __forceinline__ void wg_rs(float* d, const uint32_t* a, uint64_t db, int sd){
  if constexpr (N==24) wgmma_rs_n24<TB>(d,a,db,sd);
  if constexpr (N==48) wgmma_rs_n48<TB>(d,a,db,sd);
  if constexpr (N==64) wgmma_rs_n64<TB>(d,a,db,sd);
  if constexpr (N==80) wgmma_rs_n80<TB>(d,a,db,sd);
  if constexpr (N==96) wgmma_rs_n96<TB>(d,a,db,sd);
  if constexpr (N==128) wgmma_rs_n128<TB>(d,a,db,sd);
  if constexpr (N==160) wgmma_rs_n160<TB>(d,a,db,sd);
  if constexpr (N==192) wgmma_rs_n192<TB>(d,a,db,sd);
  if constexpr (N==224) wgmma_rs_n224<TB>(d,a,db,sd);
}
__device__ __forceinline__ void x_chk10(uint32_t* r, const uint8_t* p, uint32_t par) {
  asm volatile("{.reg .pred p; .reg .b32 m, k, n; .reg .b64 t; mov.u32 n, 0; xor.b32 m, %0, %21; xor.b32 k, %2, %21; lop3.b32 m, m, %4, %21, 0xF6; lop3.b32 k, k, %6, %21, 0xF6; lop3.b32 m, m, %8, %21, 0xF6; lop3.b32 k, k, %10, %21, 0xF6; lop3.b32 m, m, %12, %21, 0xF6; lop3.b32 k, k, %14, %21, 0xF6; lop3.b32 m, m, %16, %21, 0xF6; lop3.b32 k, k, %18, %21, 0xF6; lop3.b32 m, m, k, 1, 0xA8; setp.ne.u32 p, m, 0; vote.sync.any.pred p, p, 0xffffffff; add.u32 n, n, 1; setp.lt.and.u32 p, n, 4194304, p; @!p bra.uni XD%=;\nXL%=: ld.relaxed.gpu.global.b64 t, [%20+0]; mov.b64 {%0,%1}, t; ld.relaxed.gpu.global.b64 t, [%20+256]; mov.b64 {%2,%3}, t; ld.relaxed.gpu.global.b64 t, [%20+512]; mov.b64 {%4,%5}, t; ld.relaxed.gpu.global.b64 t, [%20+768]; mov.b64 {%6,%7}, t; ld.relaxed.gpu.global.b64 t, [%20+1024]; mov.b64 {%8,%9}, t; ld.relaxed.gpu.global.b64 t, [%20+1280]; mov.b64 {%10,%11}, t; ld.relaxed.gpu.global.b64 t, [%20+1536]; mov.b64 {%12,%13}, t; ld.relaxed.gpu.global.b64 t, [%20+1792]; mov.b64 {%14,%15}, t; ld.relaxed.gpu.global.b64 t, [%20+2048]; mov.b64 {%16,%17}, t; ld.relaxed.gpu.global.b64 t, [%20+2304]; mov.b64 {%18,%19}, t; xor.b32 m, %0, %21; xor.b32 k, %2, %21; lop3.b32 m, m, %4, %21, 0xF6; lop3.b32 k, k, %6, %21, 0xF6; lop3.b32 m, m, %8, %21, 0xF6; lop3.b32 k, k, %10, %21, 0xF6; lop3.b32 m, m, %12, %21, 0xF6; lop3.b32 k, k, %14, %21, 0xF6; lop3.b32 m, m, %16, %21, 0xF6; lop3.b32 k, k, %18, %21, 0xF6; lop3.b32 m, m, k, 1, 0xA8; setp.ne.u32 p, m, 0; vote.sync.any.pred p, p, 0xffffffff; add.u32 n, n, 1; setp.lt.and.u32 p, n, 4194304, p; @p bra.uni XL%=;\nXD%=: }"
  : "+r"(r[0]), "+r"(r[1]), "+r"(r[2]), "+r"(r[3]), "+r"(r[4]), "+r"(r[5]), "+r"(r[6]), "+r"(r[7]), "+r"(r[8]), "+r"(r[9]), "+r"(r[10]), "+r"(r[11]), "+r"(r[12]), "+r"(r[13]), "+r"(r[14]), "+r"(r[15]), "+r"(r[16]), "+r"(r[17]), "+r"(r[18]), "+r"(r[19])
  : "l"(p), "r"(par) : "memory");
}
__device__ __forceinline__ void x_chk20(uint32_t* r, const uint8_t* p, uint32_t par) {
  asm volatile("{.reg .pred p; .reg .b32 m, k, n; .reg .b64 t; mov.u32 n, 0; xor.b32 m, %0, %41; xor.b32 k, %2, %41; lop3.b32 m, m, %4, %41, 0xF6; lop3.b32 k, k, %6, %41, 0xF6; lop3.b32 m, m, %8, %41, 0xF6; lop3.b32 k, k, %10, %41, 0xF6; lop3.b32 m, m, %12, %41, 0xF6; lop3.b32 k, k, %14, %41, 0xF6; lop3.b32 m, m, %16, %41, 0xF6; lop3.b32 k, k, %18, %41, 0xF6; lop3.b32 m, m, %20, %41, 0xF6; lop3.b32 k, k, %22, %41, 0xF6; lop3.b32 m, m, %24, %41, 0xF6; lop3.b32 k, k, %26, %41, 0xF6; lop3.b32 m, m, %28, %41, 0xF6; lop3.b32 k, k, %30, %41, 0xF6; lop3.b32 m, m, %32, %41, 0xF6; lop3.b32 k, k, %34, %41, 0xF6; lop3.b32 m, m, %36, %41, 0xF6; lop3.b32 k, k, %38, %41, 0xF6; lop3.b32 m, m, k, 1, 0xA8; setp.ne.u32 p, m, 0; vote.sync.any.pred p, p, 0xffffffff; add.u32 n, n, 1; setp.lt.and.u32 p, n, 4194304, p; @!p bra.uni XD%=;\nXL%=: ld.relaxed.gpu.global.b64 t, [%40+0]; mov.b64 {%0,%1}, t; ld.relaxed.gpu.global.b64 t, [%40+256]; mov.b64 {%2,%3}, t; ld.relaxed.gpu.global.b64 t, [%40+512]; mov.b64 {%4,%5}, t; ld.relaxed.gpu.global.b64 t, [%40+768]; mov.b64 {%6,%7}, t; ld.relaxed.gpu.global.b64 t, [%40+1024]; mov.b64 {%8,%9}, t; ld.relaxed.gpu.global.b64 t, [%40+1280]; mov.b64 {%10,%11}, t; ld.relaxed.gpu.global.b64 t, [%40+1536]; mov.b64 {%12,%13}, t; ld.relaxed.gpu.global.b64 t, [%40+1792]; mov.b64 {%14,%15}, t; ld.relaxed.gpu.global.b64 t, [%40+2048]; mov.b64 {%16,%17}, t; ld.relaxed.gpu.global.b64 t, [%40+2304]; mov.b64 {%18,%19}, t; ld.relaxed.gpu.global.b64 t, [%40+2560]; mov.b64 {%20,%21}, t; ld.relaxed.gpu.global.b64 t, [%40+2816]; mov.b64 {%22,%23}, t; ld.relaxed.gpu.global.b64 t, [%40+3072]; mov.b64 {%24,%25}, t; ld.relaxed.gpu.global.b64 t, [%40+3328]; mov.b64 {%26,%27}, t; ld.relaxed.gpu.global.b64 t, [%40+3584]; mov.b64 {%28,%29}, t; ld.relaxed.gpu.global.b64 t, [%40+3840]; mov.b64 {%30,%31}, t; ld.relaxed.gpu.global.b64 t, [%40+4096]; mov.b64 {%32,%33}, t; ld.relaxed.gpu.global.b64 t, [%40+4352]; mov.b64 {%34,%35}, t; ld.relaxed.gpu.global.b64 t, [%40+4608]; mov.b64 {%36,%37}, t; ld.relaxed.gpu.global.b64 t, [%40+4864]; mov.b64 {%38,%39}, t; xor.b32 m, %0, %41; xor.b32 k, %2, %41; lop3.b32 m, m, %4, %41, 0xF6; lop3.b32 k, k, %6, %41, 0xF6; lop3.b32 m, m, %8, %41, 0xF6; lop3.b32 k, k, %10, %41, 0xF6; lop3.b32 m, m, %12, %41, 0xF6; lop3.b32 k, k, %14, %41, 0xF6; lop3.b32 m, m, %16, %41, 0xF6; lop3.b32 k, k, %18, %41, 0xF6; lop3.b32 m, m, %20, %41, 0xF6; lop3.b32 k, k, %22, %41, 0xF6; lop3.b32 m, m, %24, %41, 0xF6; lop3.b32 k, k, %26, %41, 0xF6; lop3.b32 m, m, %28, %41, 0xF6; lop3.b32 k, k, %30, %41, 0xF6; lop3.b32 m, m, %32, %41, 0xF6; lop3.b32 k, k, %34, %41, 0xF6; lop3.b32 m, m, %36, %41, 0xF6; lop3.b32 k, k, %38, %41, 0xF6; lop3.b32 m, m, k, 1, 0xA8; setp.ne.u32 p, m, 0; vote.sync.any.pred p, p, 0xffffffff; add.u32 n, n, 1; setp.lt.and.u32 p, n, 4194304, p; @p bra.uni XL%=;\nXD%=: }"
  : "+r"(r[0]), "+r"(r[1]), "+r"(r[2]), "+r"(r[3]), "+r"(r[4]), "+r"(r[5]), "+r"(r[6]), "+r"(r[7]), "+r"(r[8]), "+r"(r[9]), "+r"(r[10]), "+r"(r[11]), "+r"(r[12]), "+r"(r[13]), "+r"(r[14]), "+r"(r[15]), "+r"(r[16]), "+r"(r[17]), "+r"(r[18]), "+r"(r[19]), "+r"(r[20]), "+r"(r[21]), "+r"(r[22]), "+r"(r[23]), "+r"(r[24]), "+r"(r[25]), "+r"(r[26]), "+r"(r[27]), "+r"(r[28]), "+r"(r[29]), "+r"(r[30]), "+r"(r[31]), "+r"(r[32]), "+r"(r[33]), "+r"(r[34]), "+r"(r[35]), "+r"(r[36]), "+r"(r[37]), "+r"(r[38]), "+r"(r[39])
  : "l"(p), "r"(par) : "memory");
}
__device__ __forceinline__ void x_chk14(uint32_t* r, const uint8_t* p, uint32_t par) {
  asm volatile("{.reg .pred p; .reg .b32 m, k, n; .reg .b64 t; mov.u32 n, 0; xor.b32 m, %0, %29; xor.b32 k, %2, %29; lop3.b32 m, m, %4, %29, 0xF6; lop3.b32 k, k, %6, %29, 0xF6; lop3.b32 m, m, %8, %29, 0xF6; lop3.b32 k, k, %10, %29, 0xF6; lop3.b32 m, m, %12, %29, 0xF6; lop3.b32 k, k, %14, %29, 0xF6; lop3.b32 m, m, %16, %29, 0xF6; lop3.b32 k, k, %18, %29, 0xF6; lop3.b32 m, m, %20, %29, 0xF6; lop3.b32 k, k, %22, %29, 0xF6; lop3.b32 m, m, %24, %29, 0xF6; lop3.b32 k, k, %26, %29, 0xF6; lop3.b32 m, m, k, 1, 0xA8; setp.ne.u32 p, m, 0; vote.sync.any.pred p, p, 0xffffffff; add.u32 n, n, 1; setp.lt.and.u32 p, n, 4194304, p; @!p bra.uni XD%=;\nXL%=: ld.relaxed.gpu.global.b64 t, [%28+0]; mov.b64 {%0,%1}, t; ld.relaxed.gpu.global.b64 t, [%28+256]; mov.b64 {%2,%3}, t; ld.relaxed.gpu.global.b64 t, [%28+512]; mov.b64 {%4,%5}, t; ld.relaxed.gpu.global.b64 t, [%28+768]; mov.b64 {%6,%7}, t; ld.relaxed.gpu.global.b64 t, [%28+1024]; mov.b64 {%8,%9}, t; ld.relaxed.gpu.global.b64 t, [%28+1280]; mov.b64 {%10,%11}, t; ld.relaxed.gpu.global.b64 t, [%28+1536]; mov.b64 {%12,%13}, t; ld.relaxed.gpu.global.b64 t, [%28+1792]; mov.b64 {%14,%15}, t; ld.relaxed.gpu.global.b64 t, [%28+2048]; mov.b64 {%16,%17}, t; ld.relaxed.gpu.global.b64 t, [%28+2304]; mov.b64 {%18,%19}, t; ld.relaxed.gpu.global.b64 t, [%28+2560]; mov.b64 {%20,%21}, t; ld.relaxed.gpu.global.b64 t, [%28+2816]; mov.b64 {%22,%23}, t; ld.relaxed.gpu.global.b64 t, [%28+3072]; mov.b64 {%24,%25}, t; ld.relaxed.gpu.global.b64 t, [%28+3328]; mov.b64 {%26,%27}, t; xor.b32 m, %0, %29; xor.b32 k, %2, %29; lop3.b32 m, m, %4, %29, 0xF6; lop3.b32 k, k, %6, %29, 0xF6; lop3.b32 m, m, %8, %29, 0xF6; lop3.b32 k, k, %10, %29, 0xF6; lop3.b32 m, m, %12, %29, 0xF6; lop3.b32 k, k, %14, %29, 0xF6; lop3.b32 m, m, %16, %29, 0xF6; lop3.b32 k, k, %18, %29, 0xF6; lop3.b32 m, m, %20, %29, 0xF6; lop3.b32 k, k, %22, %29, 0xF6; lop3.b32 m, m, %24, %29, 0xF6; lop3.b32 k, k, %26, %29, 0xF6; lop3.b32 m, m, k, 1, 0xA8; setp.ne.u32 p, m, 0; vote.sync.any.pred p, p, 0xffffffff; add.u32 n, n, 1; setp.lt.and.u32 p, n, 4194304, p; @p bra.uni XL%=;\nXD%=: }"
  : "+r"(r[0]), "+r"(r[1]), "+r"(r[2]), "+r"(r[3]), "+r"(r[4]), "+r"(r[5]), "+r"(r[6]), "+r"(r[7]), "+r"(r[8]), "+r"(r[9]), "+r"(r[10]), "+r"(r[11]), "+r"(r[12]), "+r"(r[13]), "+r"(r[14]), "+r"(r[15]), "+r"(r[16]), "+r"(r[17]), "+r"(r[18]), "+r"(r[19]), "+r"(r[20]), "+r"(r[21]), "+r"(r[22]), "+r"(r[23]), "+r"(r[24]), "+r"(r[25]), "+r"(r[26]), "+r"(r[27])
  : "l"(p), "r"(par) : "memory");
}
__device__ __forceinline__ void x_chkM(uint32_t* r, const uint8_t* p, uint32_t par) {
  asm volatile("{.reg .pred p; .reg .b32 m, k, n; .reg .b64 t; mov.u32 n, 0; xor.b32 m, %0, %33; xor.b32 k, %2, %33; lop3.b32 m, m, %4, %33, 0xF6; lop3.b32 k, k, %6, %33, 0xF6; lop3.b32 m, m, %8, %33, 0xF6; lop3.b32 k, k, %10, %33, 0xF6; lop3.b32 m, m, %12, %33, 0xF6; lop3.b32 k, k, %14, %33, 0xF6; lop3.b32 m, m, %16, %33, 0xF6; lop3.b32 k, k, %18, %33, 0xF6; lop3.b32 m, m, %20, %33, 0xF6; lop3.b32 k, k, %22, %33, 0xF6; lop3.b32 m, m, %24, %33, 0xF6; lop3.b32 k, k, %26, %33, 0xF6; lop3.b32 m, m, %28, %33, 0xF6; lop3.b32 k, k, %30, %33, 0xF6; lop3.b32 m, m, k, 1, 0xA8; setp.ne.u32 p, m, 0; vote.sync.any.pred p, p, 0xffffffff; add.u32 n, n, 1; setp.lt.and.u32 p, n, 4194304, p; @!p bra.uni XD%=;\nXL%=: ld.relaxed.gpu.global.b64 t, [%32+0]; mov.b64 {%0,%1}, t; ld.relaxed.gpu.global.b64 t, [%32+256]; mov.b64 {%2,%3}, t; ld.relaxed.gpu.global.b64 t, [%32+99328]; mov.b64 {%4,%5}, t; ld.relaxed.gpu.global.b64 t, [%32+99584]; mov.b64 {%6,%7}, t; ld.relaxed.gpu.global.b64 t, [%32+198656]; mov.b64 {%8,%9}, t; ld.relaxed.gpu.global.b64 t, [%32+198912]; mov.b64 {%10,%11}, t; ld.relaxed.gpu.global.b64 t, [%32+297984]; mov.b64 {%12,%13}, t; ld.relaxed.gpu.global.b64 t, [%32+298240]; mov.b64 {%14,%15}, t; ld.relaxed.gpu.global.b64 t, [%32+397312]; mov.b64 {%16,%17}, t; ld.relaxed.gpu.global.b64 t, [%32+397568]; mov.b64 {%18,%19}, t; ld.relaxed.gpu.global.b64 t, [%32+496640]; mov.b64 {%20,%21}, t; ld.relaxed.gpu.global.b64 t, [%32+496896]; mov.b64 {%22,%23}, t; ld.relaxed.gpu.global.b64 t, [%32+595968]; mov.b64 {%24,%25}, t; ld.relaxed.gpu.global.b64 t, [%32+596224]; mov.b64 {%26,%27}, t; ld.relaxed.gpu.global.b64 t, [%32+695296]; mov.b64 {%28,%29}, t; ld.relaxed.gpu.global.b64 t, [%32+695552]; mov.b64 {%30,%31}, t; xor.b32 m, %0, %33; xor.b32 k, %2, %33; lop3.b32 m, m, %4, %33, 0xF6; lop3.b32 k, k, %6, %33, 0xF6; lop3.b32 m, m, %8, %33, 0xF6; lop3.b32 k, k, %10, %33, 0xF6; lop3.b32 m, m, %12, %33, 0xF6; lop3.b32 k, k, %14, %33, 0xF6; lop3.b32 m, m, %16, %33, 0xF6; lop3.b32 k, k, %18, %33, 0xF6; lop3.b32 m, m, %20, %33, 0xF6; lop3.b32 k, k, %22, %33, 0xF6; lop3.b32 m, m, %24, %33, 0xF6; lop3.b32 k, k, %26, %33, 0xF6; lop3.b32 m, m, %28, %33, 0xF6; lop3.b32 k, k, %30, %33, 0xF6; lop3.b32 m, m, k, 1, 0xA8; setp.ne.u32 p, m, 0; vote.sync.any.pred p, p, 0xffffffff; add.u32 n, n, 1; setp.lt.and.u32 p, n, 4194304, p; @p bra.uni XL%=;\nXD%=: }"
  : "+r"(r[0]), "+r"(r[1]), "+r"(r[2]), "+r"(r[3]), "+r"(r[4]), "+r"(r[5]), "+r"(r[6]), "+r"(r[7]), "+r"(r[8]), "+r"(r[9]), "+r"(r[10]), "+r"(r[11]), "+r"(r[12]), "+r"(r[13]), "+r"(r[14]), "+r"(r[15]), "+r"(r[16]), "+r"(r[17]), "+r"(r[18]), "+r"(r[19]), "+r"(r[20]), "+r"(r[21]), "+r"(r[22]), "+r"(r[23]), "+r"(r[24]), "+r"(r[25]), "+r"(r[26]), "+r"(r[27]), "+r"(r[28]), "+r"(r[29]), "+r"(r[30]), "+r"(r[31])
  : "l"(p), "r"(par) : "memory");
}
__device__ __forceinline__ void x_chkL(uint32_t* r, const uint8_t* p, uint32_t par) {
  asm volatile("{.reg .pred p; .reg .b32 m, k, n; .reg .b64 t; mov.u32 n, 0; xor.b32 m, %0, %33; xor.b32 k, %2, %33; lop3.b32 m, m, %4, %33, 0xF6; lop3.b32 k, k, %6, %33, 0xF6; lop3.b32 m, m, %8, %33, 0xF6; lop3.b32 k, k, %10, %33, 0xF6; lop3.b32 m, m, %12, %33, 0xF6; lop3.b32 k, k, %14, %33, 0xF6; lop3.b32 m, m, %16, %33, 0xF6; lop3.b32 k, k, %18, %33, 0xF6; lop3.b32 m, m, %20, %33, 0xF6; lop3.b32 k, k, %22, %33, 0xF6; lop3.b32 m, m, %24, %33, 0xF6; lop3.b32 k, k, %26, %33, 0xF6; lop3.b32 m, m, %28, %33, 0xF6; lop3.b32 k, k, %30, %33, 0xF6; lop3.b32 m, m, k, 1, 0xA8; setp.ne.u32 p, m, 0; vote.sync.any.pred p, p, 0xffffffff; add.u32 n, n, 1; setp.lt.and.u32 p, n, 4194304, p; @!p bra.uni XD%=;\nXL%=: ld.relaxed.gpu.global.b64 t, [%32+0]; mov.b64 {%0,%1}, t; ld.relaxed.gpu.global.b64 t, [%32+256]; mov.b64 {%2,%3}, t; ld.relaxed.gpu.global.b64 t, [%32+512]; mov.b64 {%4,%5}, t; ld.relaxed.gpu.global.b64 t, [%32+768]; mov.b64 {%6,%7}, t; ld.relaxed.gpu.global.b64 t, [%32+99328]; mov.b64 {%8,%9}, t; ld.relaxed.gpu.global.b64 t, [%32+99584]; mov.b64 {%10,%11}, t; ld.relaxed.gpu.global.b64 t, [%32+99840]; mov.b64 {%12,%13}, t; ld.relaxed.gpu.global.b64 t, [%32+100096]; mov.b64 {%14,%15}, t; ld.relaxed.gpu.global.b64 t, [%32+198656]; mov.b64 {%16,%17}, t; ld.relaxed.gpu.global.b64 t, [%32+198912]; mov.b64 {%18,%19}, t; ld.relaxed.gpu.global.b64 t, [%32+199168]; mov.b64 {%20,%21}, t; ld.relaxed.gpu.global.b64 t, [%32+199424]; mov.b64 {%22,%23}, t; ld.relaxed.gpu.global.b64 t, [%32+297984]; mov.b64 {%24,%25}, t; ld.relaxed.gpu.global.b64 t, [%32+298240]; mov.b64 {%26,%27}, t; ld.relaxed.gpu.global.b64 t, [%32+298496]; mov.b64 {%28,%29}, t; ld.relaxed.gpu.global.b64 t, [%32+298752]; mov.b64 {%30,%31}, t; xor.b32 m, %0, %33; xor.b32 k, %2, %33; lop3.b32 m, m, %4, %33, 0xF6; lop3.b32 k, k, %6, %33, 0xF6; lop3.b32 m, m, %8, %33, 0xF6; lop3.b32 k, k, %10, %33, 0xF6; lop3.b32 m, m, %12, %33, 0xF6; lop3.b32 k, k, %14, %33, 0xF6; lop3.b32 m, m, %16, %33, 0xF6; lop3.b32 k, k, %18, %33, 0xF6; lop3.b32 m, m, %20, %33, 0xF6; lop3.b32 k, k, %22, %33, 0xF6; lop3.b32 m, m, %24, %33, 0xF6; lop3.b32 k, k, %26, %33, 0xF6; lop3.b32 m, m, %28, %33, 0xF6; lop3.b32 k, k, %30, %33, 0xF6; lop3.b32 m, m, k, 1, 0xA8; setp.ne.u32 p, m, 0; vote.sync.any.pred p, p, 0xffffffff; add.u32 n, n, 1; setp.lt.and.u32 p, n, 4194304, p; @p bra.uni XL%=;\nXD%=: }"
  : "+r"(r[0]), "+r"(r[1]), "+r"(r[2]), "+r"(r[3]), "+r"(r[4]), "+r"(r[5]), "+r"(r[6]), "+r"(r[7]), "+r"(r[8]), "+r"(r[9]), "+r"(r[10]), "+r"(r[11]), "+r"(r[12]), "+r"(r[13]), "+r"(r[14]), "+r"(r[15]), "+r"(r[16]), "+r"(r[17]), "+r"(r[18]), "+r"(r[19]), "+r"(r[20]), "+r"(r[21]), "+r"(r[22]), "+r"(r[23]), "+r"(r[24]), "+r"(r[25]), "+r"(r[26]), "+r"(r[27]), "+r"(r[28]), "+r"(r[29]), "+r"(r[30]), "+r"(r[31])
  : "l"(p), "r"(par) : "memory");
}
__device__ __forceinline__ void x_chkS(uint32_t* r, const uint8_t* p, uint32_t par) {
  asm volatile("{.reg .pred p; .reg .b32 m, k, n; .reg .b64 t; mov.u32 n, 0; xor.b32 m, %0, %9; xor.b32 k, %2, %9; lop3.b32 m, m, %4, %9, 0xF6; lop3.b32 k, k, %6, %9, 0xF6; lop3.b32 m, m, k, 1, 0xA8; setp.ne.u32 p, m, 0; vote.sync.any.pred p, p, 0xffffffff; add.u32 n, n, 1; setp.lt.and.u32 p, n, 4194304, p; @!p bra.uni XD%=;\nXL%=: ld.relaxed.gpu.global.b64 t, [%8+0]; mov.b64 {%0,%1}, t; ld.relaxed.gpu.global.b64 t, [%8+8]; mov.b64 {%2,%3}, t; ld.relaxed.gpu.global.b64 t, [%8+99328]; mov.b64 {%4,%5}, t; ld.relaxed.gpu.global.b64 t, [%8+99336]; mov.b64 {%6,%7}, t; xor.b32 m, %0, %9; xor.b32 k, %2, %9; lop3.b32 m, m, %4, %9, 0xF6; lop3.b32 k, k, %6, %9, 0xF6; lop3.b32 m, m, k, 1, 0xA8; setp.ne.u32 p, m, 0; vote.sync.any.pred p, p, 0xffffffff; add.u32 n, n, 1; setp.lt.and.u32 p, n, 4194304, p; @p bra.uni XL%=;\nXD%=: }"
  : "+r"(r[0]), "+r"(r[1]), "+r"(r[2]), "+r"(r[3]), "+r"(r[4]), "+r"(r[5]), "+r"(r[6]), "+r"(r[7])
  : "l"(p), "r"(par) : "memory");
}
__device__ __forceinline__ void x_chk2(uint32_t* r, const uint8_t* p, uint32_t par) {
  asm volatile("{.reg .pred p; .reg .b32 m, k, n; .reg .b64 t; mov.u32 n, 0; xor.b32 m, %0, %5; xor.b32 k, %2, %5; lop3.b32 m, m, k, 1, 0xA8; setp.ne.u32 p, m, 0; vote.sync.any.pred p, p, 0xffffffff; add.u32 n, n, 1; setp.lt.and.u32 p, n, 4194304, p; @!p bra.uni XD%=;\nXL%=: ld.relaxed.gpu.global.b64 t, [%4+0]; mov.b64 {%0,%1}, t; ld.relaxed.gpu.global.b64 t, [%4+64]; mov.b64 {%2,%3}, t; xor.b32 m, %0, %5; xor.b32 k, %2, %5; lop3.b32 m, m, k, 1, 0xA8; setp.ne.u32 p, m, 0; vote.sync.any.pred p, p, 0xffffffff; add.u32 n, n, 1; setp.lt.and.u32 p, n, 4194304, p; @p bra.uni XL%=;\nXD%=: }"
  : "+r"(r[0]), "+r"(r[1]), "+r"(r[2]), "+r"(r[3])
  : "l"(p), "r"(par) : "memory");
}
__device__ __forceinline__ void x_chkT(uint32_t* r, const uint8_t* p, uint32_t par) {
  asm volatile("{.reg .pred p; .reg .b32 m, k, n; .reg .b64 t; mov.u32 n, 0; xor.b32 m, %0, %9; xor.b32 k, %2, %9; lop3.b32 m, m, %4, %9, 0xF6; lop3.b32 k, k, %6, %9, 0xF6; lop3.b32 m, m, k, 1, 0xA8; setp.ne.u32 p, m, 0; vote.sync.any.pred p, p, 0xffffffff; add.u32 n, n, 1; setp.lt.and.u32 p, n, 4194304, p; @!p bra.uni XD%=;\nXL%=: ld.relaxed.gpu.global.b64 t, [%8+0]; mov.b64 {%0,%1}, t; ld.relaxed.gpu.global.b64 t, [%8+8]; mov.b64 {%2,%3}, t; ld.relaxed.gpu.global.b64 t, [%8+1024]; mov.b64 {%4,%5}, t; ld.relaxed.gpu.global.b64 t, [%8+1032]; mov.b64 {%6,%7}, t; xor.b32 m, %0, %9; xor.b32 k, %2, %9; lop3.b32 m, m, %4, %9, 0xF6; lop3.b32 k, k, %6, %9, 0xF6; lop3.b32 m, m, k, 1, 0xA8; setp.ne.u32 p, m, 0; vote.sync.any.pred p, p, 0xffffffff; add.u32 n, n, 1; setp.lt.and.u32 p, n, 4194304, p; @p bra.uni XL%=;\nXD%=: }"
  : "+r"(r[0]), "+r"(r[1]), "+r"(r[2]), "+r"(r[3]), "+r"(r[4]), "+r"(r[5]), "+r"(r[6]), "+r"(r[7])
  : "l"(p), "r"(par) : "memory");
}
__device__ __forceinline__ void x_chkU(uint32_t* r, const uint8_t* p, uint32_t par) {
  asm volatile("{.reg .pred p; .reg .b32 m, k, n; .reg .b64 t; mov.u32 n, 0; xor.b32 m, %0, %33; xor.b32 k, %2, %33; lop3.b32 m, m, %4, %33, 0xF6; lop3.b32 k, k, %6, %33, 0xF6; lop3.b32 m, m, %8, %33, 0xF6; lop3.b32 k, k, %10, %33, 0xF6; lop3.b32 m, m, %12, %33, 0xF6; lop3.b32 k, k, %14, %33, 0xF6; lop3.b32 m, m, %16, %33, 0xF6; lop3.b32 k, k, %18, %33, 0xF6; lop3.b32 m, m, %20, %33, 0xF6; lop3.b32 k, k, %22, %33, 0xF6; lop3.b32 m, m, %24, %33, 0xF6; lop3.b32 k, k, %26, %33, 0xF6; lop3.b32 m, m, %28, %33, 0xF6; lop3.b32 k, k, %30, %33, 0xF6; lop3.b32 m, m, k, 1, 0xA8; setp.ne.u32 p, m, 0; vote.sync.any.pred p, p, 0xffffffff; add.u32 n, n, 1; setp.lt.and.u32 p, n, 4194304, p; @!p bra.uni XD%=;\nXL%=: ld.relaxed.gpu.global.b64 t, [%32+0]; mov.b64 {%0,%1}, t; ld.relaxed.gpu.global.b64 t, [%32+8]; mov.b64 {%2,%3}, t; ld.relaxed.gpu.global.b64 t, [%32+4096]; mov.b64 {%4,%5}, t; ld.relaxed.gpu.global.b64 t, [%32+4104]; mov.b64 {%6,%7}, t; ld.relaxed.gpu.global.b64 t, [%32+8192]; mov.b64 {%8,%9}, t; ld.relaxed.gpu.global.b64 t, [%32+8200]; mov.b64 {%10,%11}, t; ld.relaxed.gpu.global.b64 t, [%32+12288]; mov.b64 {%12,%13}, t; ld.relaxed.gpu.global.b64 t, [%32+12296]; mov.b64 {%14,%15}, t; ld.relaxed.gpu.global.b64 t, [%32+16384]; mov.b64 {%16,%17}, t; ld.relaxed.gpu.global.b64 t, [%32+16392]; mov.b64 {%18,%19}, t; ld.relaxed.gpu.global.b64 t, [%32+20480]; mov.b64 {%20,%21}, t; ld.relaxed.gpu.global.b64 t, [%32+20488]; mov.b64 {%22,%23}, t; ld.relaxed.gpu.global.b64 t, [%32+24576]; mov.b64 {%24,%25}, t; ld.relaxed.gpu.global.b64 t, [%32+24584]; mov.b64 {%26,%27}, t; ld.relaxed.gpu.global.b64 t, [%32+28672]; mov.b64 {%28,%29}, t; ld.relaxed.gpu.global.b64 t, [%32+28680]; mov.b64 {%30,%31}, t; xor.b32 m, %0, %33; xor.b32 k, %2, %33; lop3.b32 m, m, %4, %33, 0xF6; lop3.b32 k, k, %6, %33, 0xF6; lop3.b32 m, m, %8, %33, 0xF6; lop3.b32 k, k, %10, %33, 0xF6; lop3.b32 m, m, %12, %33, 0xF6; lop3.b32 k, k, %14, %33, 0xF6; lop3.b32 m, m, %16, %33, 0xF6; lop3.b32 k, k, %18, %33, 0xF6; lop3.b32 m, m, %20, %33, 0xF6; lop3.b32 k, k, %22, %33, 0xF6; lop3.b32 m, m, %24, %33, 0xF6; lop3.b32 k, k, %26, %33, 0xF6; lop3.b32 m, m, %28, %33, 0xF6; lop3.b32 k, k, %30, %33, 0xF6; lop3.b32 m, m, k, 1, 0xA8; setp.ne.u32 p, m, 0; vote.sync.any.pred p, p, 0xffffffff; add.u32 n, n, 1; setp.lt.and.u32 p, n, 4194304, p; @p bra.uni XL%=;\nXD%=: }"
  : "+r"(r[0]), "+r"(r[1]), "+r"(r[2]), "+r"(r[3]), "+r"(r[4]), "+r"(r[5]), "+r"(r[6]), "+r"(r[7]), "+r"(r[8]), "+r"(r[9]), "+r"(r[10]), "+r"(r[11]), "+r"(r[12]), "+r"(r[13]), "+r"(r[14]), "+r"(r[15]), "+r"(r[16]), "+r"(r[17]), "+r"(r[18]), "+r"(r[19]), "+r"(r[20]), "+r"(r[21]), "+r"(r[22]), "+r"(r[23]), "+r"(r[24]), "+r"(r[25]), "+r"(r[26]), "+r"(r[27]), "+r"(r[28]), "+r"(r[29]), "+r"(r[30]), "+r"(r[31])
  : "l"(p), "r"(par) : "memory");
}
__device__ __forceinline__ void x_chkV(uint32_t* r, const uint8_t* p, uint32_t par) {
  asm volatile("{.reg .pred p; .reg .b32 m, k, n; .reg .b64 s, t; mov.u32 n, 0; xor.b32 m, %0, %9; xor.b32 k, %1, %9; lop3.b32 m, m, %2, %9, 0xF6; lop3.b32 k, k, %3, %9, 0xF6; lop3.b32 m, m, %4, %9, 0xF6; lop3.b32 k, k, %5, %9, 0xF6; lop3.b32 m, m, %6, %9, 0xF6; lop3.b32 k, k, %7, %9, 0xF6; lop3.b32 m, m, k, 1, 0xA8; setp.ne.u32 p, m, 0; vote.sync.any.pred p, p, 0xffffffff; add.u32 n, n, 1; setp.lt.and.u32 p, n, 4194304, p; @!p bra.uni XD%=;\nXL%=: ld.relaxed.gpu.global.v2.b64 {s,t}, [%8+0]; mov.b64 {%0,%1}, s; mov.b64 {%2,%3}, t; ld.relaxed.gpu.global.v2.b64 {s,t}, [%8+1024]; mov.b64 {%4,%5}, s; mov.b64 {%6,%7}, t; xor.b32 m, %0, %9; xor.b32 k, %1, %9; lop3.b32 m, m, %2, %9, 0xF6; lop3.b32 k, k, %3, %9, 0xF6; lop3.b32 m, m, %4, %9, 0xF6; lop3.b32 k, k, %5, %9, 0xF6; lop3.b32 m, m, %6, %9, 0xF6; lop3.b32 k, k, %7, %9, 0xF6; lop3.b32 m, m, k, 1, 0xA8; setp.ne.u32 p, m, 0; vote.sync.any.pred p, p, 0xffffffff; add.u32 n, n, 1; setp.lt.and.u32 p, n, 4194304, p; @p bra.uni XL%=;\nXD%=: }"
  : "+r"(r[0]), "+r"(r[1]), "+r"(r[2]), "+r"(r[3]), "+r"(r[4]), "+r"(r[5]), "+r"(r[6]), "+r"(r[7])
  : "l"(p), "r"(par) : "memory");
}
constexpr int SEQ = 2048, DM = 640, FF = 1728;
constexpr int NCTA = 132;
constexpr uint32_t P1_STAGE = 47104;
constexpr uint32_t SM_WO = 0;
constexpr uint32_t HB = 11264, SM_KV0 = 161792, SM_KV1 = 94208;
constexpr uint32_t SM_Q = 68608, SM_QZ = SM_Q + 24576;
constexpr uint32_t SM_SW = 225280;
constexpr uint32_t SM_HW = 4 * P1_STAGE, SM_HX = SM_HW + 19200;
constexpr uint32_t SM_BAR = 229376;
constexpr uint32_t SM_CS1 = SM_BAR + 384;
constexpr uint32_t SM_CS2 = SM_CS1 + 960;
constexpr uint32_t SM_EP = SM_CS2 + 896;
constexpr uint32_t SM_TS = SM_EP + 16;
constexpr uint32_t SM_TOTAL = SM_TS;
enum { B_FULL1 = 0, B_KVF = 4, B_BFULL = 6  , B_WOFULL = 12, B_CS = 14, B_ZERO = 16,
       B_XR = 17,
       B_KVW = 18,
       B_H1 = 22,
       B_EMPTY1 = 23, B_BEMPTY = 27  , B_P1DONE = 33, B_COUNT = 34 };
enum { F_KV = 0, F_ZERO = 4 };
DEVI uint32_t b_slot(int s) { return (s < 4 ? s + 2 : s - 4) * 35840; }
constexpr uint32_t SM_WOL = SM_BAR - 38400;
constexpr uint32_t SM_XR = SM_KV0;
constexpr uint32_t SM_OUT = 0;
constexpr uint32_t X_O = 0, X_H = 20480, X_S = 40960, X_G = 41984, X_SIZE = 99328;

constexpr uint32_t G_ORDER = 0x76532140u;

__device__ __align__(128) uint8_t g_kv[16 * 8 * 2 * HB];
__device__ __align__(128) uint8_t g_kx[16 * 8 * 20480];
__device__ __align__(128) uint8_t g_x[16 * 8 * X_SIZE];
__device__ __align__(128) uint8_t g_p[16 * 8 * 20480];
__device__ __align__(128) uint8_t g_xs[128 * 4096];
__device__ __align__(128) uint8_t g_none[11264];
__device__ __align__(128) float g_cs1[8 * 16 * 240];
__device__ __align__(128) float g_cs2[8 * 224];
__device__ __align__(128) unsigned g_flag[(128 + 8 + 1) * 32];
__device__ unsigned long long g_ticket;
#define TS(i)
#define TSX(i)
#define TA(i)
#define TB(i)
#define TBW(i)
#define TS1(i)
#define TSW(i)
#define TSEND()

#define PL(i)
#define PFINE 0
#define PLAG 0
#define T8(i)
struct Params {
  CUtensorMap x, qkv128, qkv32, wo, w1, w2, o, xr;
  const __nv_bfloat16 *xp, *wqkvp, *wop, *w1p, *w2p;
  uint8_t* outp;
  int use_smid, never;
};

DEVI void mbar_init(uint32_t b, int c) { asm volatile("mbarrier.init.shared::cta.b64 [%0], %1;" ::"r"(b), "r"(c)); }
DEVI void mbar_expect(uint32_t b, uint32_t bytes) { asm volatile("mbarrier.arrive.expect_tx.shared::cta.b64 _, [%0], %1;" ::"r"(b), "r"(bytes) : "memory"); }
DEVI void mbar_arrive(uint32_t b) { asm volatile("mbarrier.arrive.shared::cta.b64 _, [%0];" ::"r"(b) : "memory"); }
DEVI void mbar_arrive_cta(uint32_t b, uint32_t cta) {
  asm volatile("{.reg .b32 r; mapa.shared::cluster.u32 r, %0, %1; mbarrier.arrive.shared::cluster.b64 _, [r];}" ::"r"(b), "r"(cta) : "memory");
}
constexpr uint32_t SPIN_LIMIT = 1u << 22;
DEVI void mbar_wait(uint32_t b, uint32_t ph) {
  asm volatile("{.reg .pred p; .reg .u32 n; mov.u32 n, 0;\n"
               "MW%=: mbarrier.try_wait.parity.shared::cta.b64 p, [%0], %1; add.u32 n, n, 1; setp.lt.and.u32 p, n, %2, !p; @p bra MW%=;}"
               ::"r"(b), "r"(ph), "n"(SPIN_LIMIT) : "memory");
}
DEVI bool mbar_test(uint32_t b, uint32_t ph) {
  uint32_t r;
  asm volatile("{.reg .pred p; mbarrier.test_wait.parity.shared::cta.b64 p, [%1], %2; selp.u32 %0, 1, 0, p;}" : "=r"(r) : "r"(b), "r"(ph) : "memory");
  return r;
}
DEVI unsigned ld_acq(const unsigned* p) { unsigned v; asm volatile("ld.acquire.gpu.global.u32 %0, [%1];" : "=r"(v) : "l"(p) : "memory"); return v; }
DEVI unsigned ld_rlx(const unsigned* p) { unsigned v; asm volatile("ld.relaxed.gpu.global.u32 %0, [%1];" : "=r"(v) : "l"(p) : "memory"); return v; }
DEVI void poll_flag(const unsigned* p, unsigned target) {
  uint32_t n = 0;
  while (__any_sync(0xffffffffu, (int)(ld_acq(p) - target) < 0) && ++n < SPIN_LIMIT) {}
  __syncwarp();
}
DEVI void red_release(unsigned* p) { asm volatile("red.release.gpu.global.add.u32 [%0], 1;" ::"l"(p) : "memory"); }
DEVI void fence_async() { asm volatile("fence.proxy.async.global;" ::: "memory"); }
DEVI void fence_async_smem() { asm volatile("fence.proxy.async.shared::cta;" ::: "memory"); }
DEVI bool elect() {
  uint32_t p;
  asm volatile("{.reg .pred p; elect.sync _|p, 0xffffffff; selp.u32 %0, 1, 0, p;}" : "=r"(p));
  return p;
}
DEVI void tma2d(uint32_t dst, const CUtensorMap* m, int x, int y, uint32_t bar) {
  asm volatile("cp.async.bulk.tensor.2d.shared::cluster.global.mbarrier::complete_tx::bytes [%0], [%1, {%3, %4}], [%2];"
               ::"r"(dst), "l"(m), "r"(bar), "r"(x), "r"(y) : "memory");
}
DEVI void tma3d(uint32_t dst, const CUtensorMap* m, int x, int y, int z, uint32_t bar) {
  asm volatile("cp.async.bulk.tensor.3d.shared::cluster.global.mbarrier::complete_tx::bytes [%0], [%1, {%3, %4, %5}], [%2];"
               ::"r"(dst), "l"(m), "r"(bar), "r"(x), "r"(y), "r"(z) : "memory");
}
DEVI void tma3d_mc(uint32_t dst, const CUtensorMap* m, int x, int y, int z, uint32_t bar) {
  asm volatile("cp.async.bulk.tensor.3d.shared::cluster.global.mbarrier::complete_tx::bytes.multicast::cluster [%0], [%1, {%3, %4, %5}], [%2], %6;"
               ::"r"(dst), "l"(m), "r"(bar), "r"(x), "r"(y), "r"(z), "h"((uint16_t)3) : "memory");
}
DEVI void bulk_g2s(uint32_t dst, const void* src, uint32_t bytes, uint32_t bar) {
  asm volatile("cp.async.bulk.shared::cluster.global.mbarrier::complete_tx::bytes [%0], [%1], %2, [%3];"
               ::"r"(dst), "l"(src), "r"(bytes), "r"(bar) : "memory");
}
DEVI void bulk_prefetch(const void* src, uint32_t bytes) { asm volatile("cp.async.bulk.prefetch.L2.global [%0], %1;" ::"l"(src), "r"(bytes) : "memory"); }
DEVI void wg_fence() { asm volatile("wgmma.fence.sync.aligned;" ::: "memory"); }
DEVI void wg_commit() { asm volatile("wgmma.commit_group.sync.aligned;" ::: "memory"); }
template <int N> DEVI void wg_wait() { asm volatile("wgmma.wait_group.sync.aligned %0;" ::"n"(N) : "memory"); }
template <int N> DEVI void reg_fence(float* a) {
#pragma unroll
  for (int i = 0; i < N; i++) asm volatile("" : "+f"(a[i])::"memory");
}
template <int N> DEVI void reg_fence_u(uint32_t* a) {
#pragma unroll
  for (int i = 0; i < N; i++) asm volatile("" : "+r"(a[i])::"memory");
}
DEVI uint64_t mkdesc(uint32_t addr, uint32_t lbo, uint32_t sbo, uint32_t swz) {
  return (uint64_t)((addr >> 4) & 0x3FFF) | ((uint64_t)(lbo >> 4) << 16) | ((uint64_t)(sbo >> 4) << 32) | ((uint64_t)swz << 62);
}
DEVI uint32_t pack2(float lo, float hi) { uint32_t r; asm("cvt.rn.bf16x2.f32 %0, %1, %2;" : "=r"(r) : "f"(hi), "f"(lo)); return r; }
DEVI float bf_lo(uint32_t v) { return __uint_as_float(v << 16); }
DEVI float bf_hi(uint32_t v) { return __uint_as_float(v & 0xffff0000u); }
DEVI float ex2(float x) { float r; asm("ex2.approx.ftz.f32 %0, %1;" : "=f"(r) : "f"(x)); return r; }
DEVI float rcp_a(float x) { float r; asm("rcp.approx.ftz.f32 %0, %1;" : "=f"(r) : "f"(x)); return r; }
DEVI float tanh_a(float x) { float r; asm("tanh.approx.f32 %0, %1;" : "=f"(r) : "f"(x)); return r; }
DEVI void sts32(uint32_t a, uint32_t v) { asm volatile("st.shared.u32 [%0], %1;" ::"r"(a), "r"(v) : "memory"); }
DEVI float2 lds64f(uint32_t a) { float2 v; asm volatile("ld.shared.v2.f32 {%0,%1}, [%2];" : "=f"(v.x), "=f"(v.y) : "r"(a)); return v; }
DEVI float2 lds64c(uint32_t a) { float2 v; asm("ld.shared.v2.f32 {%0,%1}, [%2];" : "=f"(v.x), "=f"(v.y) : "r"(a)); return v; }
DEVI uint32_t lds32(uint32_t a) { uint32_t v; asm volatile("ld.shared.u32 %0, [%1];" : "=r"(v) : "r"(a)); return v; }
DEVI uint4 lds128(uint32_t a) { uint4 v; asm volatile("ld.shared.v4.u32 {%0,%1,%2,%3}, [%4];" : "=r"(v.x), "=r"(v.y), "=r"(v.z), "=r"(v.w) : "r"(a)); return v; }
DEVI float4 ldcg128f(const void* p) { float4 v; asm volatile("ld.global.cg.v4.f32 {%0,%1,%2,%3}, [%4];" : "=f"(v.x), "=f"(v.y), "=f"(v.z), "=f"(v.w) : "l"(p) : "memory"); return v; }
DEVI uint4 ldnc128(const void* p) { uint4 v; asm volatile("ld.global.nc.v4.u32 {%0,%1,%2,%3}, [%4];" : "=r"(v.x), "=r"(v.y), "=r"(v.z), "=r"(v.w) : "l"(p)); return v; }
DEVI void cp16(uint32_t d, const void* p) { asm volatile("cp.async.cg.shared.global [%0], [%1], 16;" ::"r"(d), "l"(p) : "memory"); }
DEVI void ldsm4(uint32_t* r, uint32_t a) {
  asm volatile("ldmatrix.sync.aligned.m8n8.x4.shared.b16 {%0,%1,%2,%3}, [%4];" : "=r"(r[0]), "=r"(r[1]), "=r"(r[2]), "=r"(r[3]) : "r"(a) : "memory");
}
DEVI void stsm4(uint32_t a, uint32_t r0, uint32_t r1, uint32_t r2, uint32_t r3) {
  asm volatile("stmatrix.sync.aligned.m8n8.x4.shared.b16 [%0], {%1,%2,%3,%4};" ::"r"(a), "r"(r0), "r"(r1), "r"(r2), "r"(r3) : "memory");
}
DEVI void stsm2(uint32_t a, uint32_t r0, uint32_t r1) {
  asm volatile("stmatrix.sync.aligned.m8n8.x2.shared.b16 [%0], {%1,%2};" ::"r"(a), "r"(r0), "r"(r1) : "memory");
}
DEVI void ldx(uint32_t* r, const uint8_t* p) {

  asm volatile("{.reg .b64 t; ld.relaxed.gpu.global.b64 t, [%2]; mov.b64 {%0,%1}, t;}" : "=r"(r[0]), "=r"(r[1]) : "l"(p) : "memory");

}
DEVI void ldx2(uint32_t* r, const uint8_t* p) {
  asm volatile("{.reg .b64 s, t; ld.relaxed.gpu.global.v2.b64 {s,t}, [%4]; mov.b64 {%0,%1}, s; mov.b64 {%2,%3}, t;}" : "=r"(r[0]), "=r"(r[1]), "=r"(r[2]), "=r"(r[3]) : "l"(p) : "memory");
}
DEVI float rsq_a(float x) { float y; asm("rsqrt.approx.ftz.f32 %0, %1;" : "=f"(y) : "f"(x)); return y; }
DEVI void stx(uint8_t* p, uint32_t a, uint32_t b) { asm volatile("{.reg .b64 t; mov.b64 t, {%1,%2}; st.relaxed.gpu.global.b64 [%0], t;}" ::"l"(p), "r"(a), "r"(b) : "memory"); }
DEVI void stxp(uint8_t* p, uint32_t a, uint32_t b, bool on) {
  asm volatile("{.reg .pred q; .reg .b64 t; setp.ne.u32 q, %3, 0; mov.b64 t, {%1,%2}; @q st.relaxed.gpu.global.b64 [%0], t;}" ::"l"(p), "r"(a), "r"(b), "r"((uint32_t)on) : "memory");
}
DEVI void stx2(uint8_t* p, uint64_t v) { asm volatile("st.relaxed.gpu.global.v2.b64 [%0], {%1,%1};" ::"l"(p), "l"(v) : "memory"); }
DEVI void probe(uint32_t& seen, uint32_t need, const uint8_t* p, uint32_t par) {
  asm volatile("{.reg .pred p; .reg .b32 m, n; mov.u32 n, 0;\n"
               "PC%=: lop3.b32 m, %0, %1, 0, 0x0C; setp.ne.u32 p, m, 0; add.u32 n, n, 1; setp.lt.and.u32 p, n, %4, p; @!p bra.uni PD%=;\n"
               "ld.relaxed.gpu.global.b32 m, [%2]; lop3.b32 m, m, %3, 1, 0x28; setp.eq.u32 p, m, 0; vote.sync.ballot.b32 %0, p, 0xffffffff; bra.uni PC%=;\n"
               "PD%=: }" : "+r"(seen) : "r"(need), "l"(p), "r"(par), "n"(SPIN_LIMIT) : "memory");
}
DEVI uint32_t peek(const uint8_t* p) { uint32_t v; asm volatile("ld.relaxed.gpu.global.b32 %0, [%1];" : "=r"(v) : "l"(p) : "memory"); return v; }
DEVI uint32_t peeked(uint32_t v, uint32_t par) { return __ballot_sync(0xffffffffu, ((v ^ par) & 1) == 0); }
DEVI int lane_again() { int l; asm volatile("mov.u32 %0, %%laneid;" : "=r"(l)); return l; }
DEVI uint32_t tag(uint32_t a, uint32_t par) { return (a & ~1u) | par; }
template <int N, int STEP> DEVI void x_load(uint32_t* r, const uint8_t* p) {
#pragma unroll
  for (int j = 0; j < N; j++) ldx(r + 2 * j, p + j * STEP);
}
template <int N> DEVI void reg_def(float* a) {
#pragma unroll
  for (int i = 0; i < N; i++) asm volatile("" : "=f"(a[i]));
}
DEVI void flag_set(unsigned* p, unsigned v) { asm volatile("st.release.gpu.global.u32 [%0], %1;" ::"l"(p), "r"(v) : "memory"); }
DEVI void acc8(float* s, const uint4 v) {
  s[0] += bf_lo(v.x); s[1] += bf_hi(v.x); s[2] += bf_lo(v.y); s[3] += bf_hi(v.y);
  s[4] += bf_lo(v.z); s[5] += bf_hi(v.z); s[6] += bf_lo(v.w); s[7] += bf_hi(v.w);
}

#define PEERX 0
#define ROWX 0
#define LAG5 13
#define LEAD5 15
#define EREL 3
#define W2T 0
#define PADH 51
#define PADZ 0
#define PAD5 0
#define PAD0 0
#define PAD4 0
#define NEED11 32
#define NEED12 192
#define NEED13 0
#define PK12 0
#define EARLY0 1
#define PADE 0
#define PADA 0
#define PKT -1
#define PKK -1
#define PK5 0
#define BP15 0
#define BP9 10
#define BAL5 1
#define STEP5 7
#define FEWV 0
#define HRP (STEP5 == 3 || STEP5 == 4 ? 13 : 14)
#define OUTS 1
#define TAILR 0
#define STAGU 0
#define WOS 0
#define BFL 0
#define RL3 -1
#define RL4 2
#define RL5 2
#define PPW 1
#define QSPLIT 0
#define LPOS 3
#define PREW 1
#define KVE 2
#define STAGP 0
#define LAG 2
#define LAG0 2
#define EOB 0
#define NOREDO 0
#define PKA 8
#define REL 1
#define PACE 0
#define XRE 1
#define E0A 6
#define E2A 4
#define PROBE (27 + 128)
#define EARLY5 0
#define DEFER5 1
#define PEEK5 20
#define SPL5 7
#define NEED5 28
#define EPI 0
#define NOFF 12
#define SEG4 0x2488
#define CSD 2
#define STN 5
#define LAGE 0
#define TAIL5 0
#define UP0 2
#define UP1 4
#define OFN 6
#define RA5 0
#define RB5 0
#define FIRST 1
#define PRO 0
#define PRE0 0
#define PACE1 3
#define ORD1 2
#define PIN1 0
#define XPF 0
#define XPO 512
#define REL1 0
#define XG 1
#define XP 7
#define XLD 0
#define XD 1
#define PFIT2 PFIT
#define KC 0
#define KF 0
#define KN 0
#define KW 0
#define KW0 4
#define XSP 4
#define XL4 6
#define XF4 7
#define TW 0
#define SPARE2 3000
#define CU 1
#define XC0 (XST >= 5 ? 3 : 4)
#define XPIN 1
#define CSV 1
#define XPK 9
#define CSE 2
#define XF3 0
#define XSW 0
#define XE 0
#define XB 0
#define XST 6
#define PFIT 2
template <bool V> struct BoolC { static constexpr bool value = V; };

constexpr float SM_C = 0.22360679774997896f * 1.4426950408889634f;

DEVI void attn_pv(float* o, uint32_t* p, uint64_t dv) {
#pragma unroll
  for (int j = 0; j < 4; j++) wg_rs<24, 1>(o + 12 * (j & 1), p + 4 * j, dv + 16 * j, 1);
}
DEVI void attn_pv0(float* o, uint32_t* pd, uint32_t* pt, uint64_t dd, uint64_t dt) {
  wgmma_rz_n24<1>(o, pd, dd); wgmma_rz_n24<1>(o + 12, pt, dt);
#pragma unroll
  for (int j = 1; j < 4; j++) { wg_rs<24, 1>(o, pd + 4 * j, dd + 16 * j, 1); wg_rs<24, 1>(o + 12, pt + 4 * j, dt + 16 * j, 1); }
}
DEVI void bb(uint32_t z) {
  asm volatile("{.reg .pred p; .reg .b32 r; setp.eq.u32 p, %0, 0; @p bra.uni BBD%=; BBL%=: ld.volatile.shared.u32 r, [%0]; setp.ne.u32 p, r, 0; @p bra.uni BBL%=; BBD%=: }" ::"r"(z) : "memory");
}
template <int N> DEVI void pad(uint32_t z) {
  if (N > 0 && z) {
#pragma unroll
    for (int i = 0; i < N; i++) asm volatile("st.volatile.shared.u32 [%0], %0;" ::"r"(z) : "memory");
  }
}
DEVI uint32_t bbv(uint32_t z, uint32_t x) {
  asm volatile("{.reg .pred p; setp.eq.u32 p, %1, 0; @p bra.uni BBD%=; BBL%=: ld.volatile.shared.u32 %0, [%1]; setp.ne.u32 p, %0, 0; @p bra.uni BBL%=; BBD%=: }" : "+r"(x) : "r"(z) : "memory");
  return x;
}
DEVI void bbf8(uint32_t z, const float* y) {
  asm volatile("{.reg .pred p; .reg .b32 r; setp.eq.u32 p, %8, 0; @p bra.uni BBD%=; lop3.b32 r, %0, %1, %2, 0x96; lop3.b32 r, r, %3, %4, 0x96; lop3.b32 r, r, %5, %6, 0x96; xor.b32 r, r, %7;  st.volatile.shared.u32 [%8], r;"
               "BBL%=: ld.volatile.shared.u32 r, [%8]; setp.ne.u32 p, r, 0; @p bra.uni BBL%=; BBD%=: }"
               :: "r"(__float_as_uint(y[0])), "r"(__float_as_uint(y[1])), "r"(__float_as_uint(y[2])), "r"(__float_as_uint(y[3])), "r"(__float_as_uint(y[4])), "r"(__float_as_uint(y[5])), "r"(__float_as_uint(y[6])), "r"(__float_as_uint(y[7])), "r"(z) : "memory");
}
DEVI void bbf12(uint32_t z, const float* y) {
  asm volatile("{.reg .pred p; .reg .b32 r; setp.eq.u32 p, %12, 0; @p bra.uni BBD%=; lop3.b32 r, %0, %1, %2, 0x96; lop3.b32 r, r, %3, %4, 0x96; lop3.b32 r, r, %5, %6, 0x96; lop3.b32 r, r, %7, %8, 0x96; lop3.b32 r, r, %9, %10, 0x96; xor.b32 r, r, %11;  st.volatile.shared.u32 [%12], r;"
               "BBL%=: ld.volatile.shared.u32 r, [%12]; setp.ne.u32 p, r, 0; @p bra.uni BBL%=; BBD%=: }"
               :: "r"(__float_as_uint(y[0])), "r"(__float_as_uint(y[1])), "r"(__float_as_uint(y[2])), "r"(__float_as_uint(y[3])), "r"(__float_as_uint(y[4])), "r"(__float_as_uint(y[5])), "r"(__float_as_uint(y[6])), "r"(__float_as_uint(y[7])), "r"(__float_as_uint(y[8])), "r"(__float_as_uint(y[9])), "r"(__float_as_uint(y[10])), "r"(__float_as_uint(y[11])), "r"(z) : "memory");
}
DEVI void bbf20(uint32_t z, const float* y) {
  asm volatile("{.reg .pred p; .reg .b32 r; setp.eq.u32 p, %20, 0; @p bra.uni BBD%=; lop3.b32 r, %0, %1, %2, 0x96; lop3.b32 r, r, %3, %4, 0x96; lop3.b32 r, r, %5, %6, 0x96; lop3.b32 r, r, %7, %8, 0x96; lop3.b32 r, r, %9, %10, 0x96; lop3.b32 r, r, %11, %12, 0x96; lop3.b32 r, r, %13, %14, 0x96; lop3.b32 r, r, %15, %16, 0x96; lop3.b32 r, r, %17, %18, 0x96; xor.b32 r, r, %19;  st.volatile.shared.u32 [%20], r;"
               "BBL%=: ld.volatile.shared.u32 r, [%20]; setp.ne.u32 p, r, 0; @p bra.uni BBL%=; BBD%=: }"
               :: "r"(__float_as_uint(y[0])), "r"(__float_as_uint(y[1])), "r"(__float_as_uint(y[2])), "r"(__float_as_uint(y[3])), "r"(__float_as_uint(y[4])), "r"(__float_as_uint(y[5])), "r"(__float_as_uint(y[6])), "r"(__float_as_uint(y[7])), "r"(__float_as_uint(y[8])), "r"(__float_as_uint(y[9])), "r"(__float_as_uint(y[10])), "r"(__float_as_uint(y[11])), "r"(__float_as_uint(y[12])), "r"(__float_as_uint(y[13])), "r"(__float_as_uint(y[14])), "r"(__float_as_uint(y[15])), "r"(__float_as_uint(y[16])), "r"(__float_as_uint(y[17])), "r"(__float_as_uint(y[18])), "r"(__float_as_uint(y[19])), "r"(z) : "memory");
}
template <int N> DEVI void bbuse(uint32_t z, const float* y) {
  if (__builtin_expect(z != 0, 0)) {
    uint32_t r = 0;
#pragma unroll
    for (int i = 0; i < N; i++) r ^= __float_as_uint(y[i]);
    asm volatile("{.reg .pred p; .reg .b32 r; st.volatile.shared.u32 [%0], %1; BBL%=: ld.volatile.shared.u32 r, [%0]; setp.ne.u32 p, r, 0; @p bra.uni BBL%=;}" ::"r"(z), "r"(r) : "memory");
  }
}
DEVI void bbf48(uint32_t z, const float* y) { bbuse<48>(z, y); }
DEVI void bbf32(uint32_t z, const float* y) { bbuse<32>(z, y); }
template <int N> DEVI void bbf(uint32_t z, const float* y) { if constexpr (N == 8) bbf8(z, y); if constexpr (N == 12) bbf12(z, y); }
DEVI void bbp2(uint32_t z, float* y) {
  asm volatile("{.reg .pred p; .reg .b32 r; .reg .b64 a; setp.eq.u32 p, %2, 0; @p bra.uni BBD%=; cvt.u64.u32 a, %2;"
               "BBL%=: ld.volatile.global.u32 r, [a]; setp.ne.u32 p, r, 0; @p bra.uni BBL%=; mov.b32 %0, r; mov.b32 %1, r; BBD%=: }"
               : "+f"(y[0]), "+f"(y[1]) : "r"(z) : "memory");
}
DEVI void bbp4(uint32_t z, float* y) {
  asm volatile("{.reg .pred p; .reg .b32 r; .reg .b64 a; setp.eq.u32 p, %4, 0; @p bra.uni BBD%=; cvt.u64.u32 a, %4;"
               "BBL%=: ld.volatile.global.u32 r, [a]; setp.ne.u32 p, r, 0; @p bra.uni BBL%=; mov.b32 %0, r; mov.b32 %1, r; mov.b32 %2, r; mov.b32 %3, r; BBD%=: }"
               : "+f"(y[0]), "+f"(y[1]), "+f"(y[2]), "+f"(y[3]) : "r"(z) : "memory");
}
DEVI void bbp6(uint32_t z, uint32_t* x, float* y) {
  asm volatile("{.reg .pred p; .reg .b32 r; .reg .b64 a; setp.eq.u32 p, %6, 0; @p bra.uni BBD%=; cvt.u64.u32 a, %6;"
               "BBL%=: ld.volatile.global.u32 r, [a]; setp.ne.u32 p, r, 0; @p bra.uni BBL%=; mov.b32 %0, r; mov.b32 %1, r; mov.b32 %2, r; mov.b32 %3, r; mov.b32 %4, r; mov.b32 %5, r; BBD%=: }"
               : "+r"(x[0]), "+r"(x[1]), "+r"(x[2]), "+r"(x[3]), "+f"(y[0]), "+f"(y[1]) : "r"(z) : "memory");
}
DEVI void bb4(uint32_t z, uint32_t* x) {
  asm volatile("{.reg .pred p; .reg .b32 r; .reg .b64 a; setp.eq.u32 p, %4, 0; @p bra.uni BBD%=; cvt.u64.u32 a, %4;"
               "BBL%=: ld.volatile.global.u32 r, [a]; setp.ne.u32 p, r, 0; @p bra.uni BBL%=; mov.b32 %0, r; mov.b32 %1, r; mov.b32 %2, r; mov.b32 %3, r; BBD%=: }"
               : "+r"(x[0]), "+r"(x[1]), "+r"(x[2]), "+r"(x[3]) : "r"(z) : "memory");
}
template <int N> DEVI void attn_pre(float* s) {
#pragma unroll
  for (int i = 0; i < 2 * N; i++) asm volatile("ex2.approx.ftz.f32 %0, %0;" : "+f"(s[i]));
  reg_fence<2 * N>(s);
}
template <int A = 0, int B = 16, int PRE = 0> DEVI void attn_exp(float* s, uint32_t* p) {
  reg_fence<2 * (B - A)>(s + 2 * A);
#pragma unroll
  for (int i = A; i < B; i++) p[i] = i < PRE ? pack2(s[2 * i], s[2 * i + 1]) : pack2(ex2(s[2 * i]), ex2(s[2 * i + 1]));
  reg_fence_u<B - A>(p + A);
}

DEVI constexpr uint64_t w2off(int kk) { return kk < 3 ? kk * 64 : kk == 3 ? 192 + ((uint64_t)((14848 - 512) >> 4) << 32) : (17920 + 512) / 16 + (kk - 4) * 64; }

DEVI constexpr uint64_t w1off(int kk) { return kk < 2 ? kk * 64 : kk == 2 ? 128 + ((uint64_t)((15872 - 512) >> 4) << 32) : (17920 + 512) / 16 + (kk - 3) * 64; }

constexpr int CUV = CU;
__global__ void __launch_bounds__(384, 1) fused_kernel(const __grid_constant__ Params P) {
  extern __shared__ __align__(1024) uint8_t smem[];
  const uint32_t sb = (uint32_t)__cvta_generic_to_shared(smem);
  const uint32_t bar = sb + SM_BAR;
#define BAR(i) (bar + 8u * (i))
  const int warp = __shfl_sync(0xffffffffu, threadIdx.x >> 5, 0), lane = threadIdx.x & 31;
  uint32_t rank; asm volatile("mov.u32 %0, %%cluster_ctarank;" : "=r"(rank));
  int grp, c;
  if (P.use_smid) {
    uint32_t smid; asm volatile("mov.u32 %0, %%smid;" : "=r"(smid));
    if (smid < 64) { grp = (smid & 15) >> 1; c = smid >> 4; }
    else if (smid < 120) { grp = ((smid - 64) % 14) / 2 + 1; c = 4 + (smid - 64) / 14; }
    else if (smid < 124) { grp = -1; c = smid - 120; }
    else { grp = 0; c = 4 + ((smid - 124) >> 1); }
  } else {
    const int pr = blockIdx.x >> 1;
    grp = pr < 64 ? pr >> 3 : -1; c = pr < 64 ? pr & 7 : blockIdx.x - 128;
  }
  if (grp < 0) {
    pad<PADZ>(P.never);
    float* red = reinterpret_cast<float*>(smem);
    unsigned ep = 0;
    if (warp == 0) ep = __shfl_sync(0xffffffffu, lane == 0 ? (unsigned)(atomicAdd(&g_ticket, 1ull) / NCTA) + 1 : 0u, 0);
    const int cc = threadIdx.x % 54, rg = threadIdx.x / 54 - 2;
    if (rg >= 0 && rg < 5) {
      float a[8] = {0.f, 0.f, 0.f, 0.f, 0.f, 0.f, 0.f, 0.f};
      const __nv_bfloat16* src = P.w1p + c * 432 + cc * 8 + rg * FF;
#pragma unroll 1
      for (int r0 = 0; r0 < 16; r0++, src += 40 * FF) {
        uint4 v[8];
#pragma unroll
        for (int i = 0; i < 8; i++) v[i] = ldnc128(src + 5 * i * FF);
#pragma unroll
        for (int i = 0; i < 8; i++) acc8(a, v[i]);
      }
#pragma unroll
      for (int i = 0; i < 8; i++) red[rg * 432 + cc * 8 + i] = a[i];
    } else if (warp == 1 && elect()) {
      const uint32_t t0 = clock();
      while ((uint32_t)clock() - t0 < SPARE2) {}
#pragma unroll 1
      for (int i = 0; i < 76; i++) {
        const int m = i < 32 ? 2 : i < 44 ? 1 : 3;
        if (W2T && i == 44) while ((uint32_t)clock() - t0 < W2T) {}
        bulk_prefetch((const uint8_t*)(&P.wqkvp)[m] + c * (m == 1 ? 204800 : 552960) + (i < 32 ? i : i < 44 ? i - 32 : i - 44) * 17280, i == 43 ? 204800 - 11 * 17280 : 17280);
      }
    }
    __syncthreads();
#pragma unroll 1
    for (int i = threadIdx.x; i < 432; i += 384) {
      float a = 0.f;
#pragma unroll
      for (int r = 0; r < 5; r++) a += red[r * 432 + i];
      g_cs2[c * 432 + i] = a;
    }
    __syncthreads();
    if (threadIdx.x == 0) red_release(&g_flag[136 * 32]);
    if (warp == 0) poll_flag(&g_flag[(128 + (lane & 7)) * 32], 16 * ep);
    return;
  }
  c = __shfl_sync(0xffffffffu, c, 0);
  const int rb = __shfl_sync(0xffffffffu, grp * 2 + rank, 0), role = rb * 8 + c;
  unsigned long long tk = 0;
  auto ticket = [&]() {
    if (threadIdx.x == 63) {
      asm volatile("atom.relaxed.gpu.global.add.u64 %0, [%1], 1;" : "=l"(tk) : "l"(&g_ticket) : "memory");
      asm volatile("red.relaxed.gpu.global.add.u32 [%0], 1;" ::"l"(&g_flag[(128 + c) * 32]) : "memory");
    }
    __syncwarp();
  };
  auto cs_rows = [&]() {
    if (lane < 30) {
      const __nv_bfloat16* src = P.wqkvp + (size_t)(40 * rb + warp - 1) * (3 * DM) + (lane / 10) * DM + 80 * c + (lane % 10) * 8;
#pragma unroll CUV
      for (int i = warp == 1 ? 0 : 1; i < 14; i++) cp16(sb + SM_HW + (warp - 1) * 480 + lane * 16 + (13 - i) * 1440, src + (13 - i) * (9 * DM));
    }
    asm volatile("cp.async.commit_group;" ::: "memory");
    if (XST < 3) ticket();
  };
  if (warp == 0) {
    if (elect()) {
      T8(40);
#pragma unroll
      for (int k = 0; k < 4; k++) mbar_init(BAR(B_FULL1 + k), 1);
      asm volatile("fence.mbarrier_init.release.cluster;" ::: "memory");
      mbar_expect(BAR(B_FULL1), P1_STAGE);
      T8(41);
      tma2d(sb, &P.x, 0, 128 * rb, BAR(B_FULL1));
      T8(42);
#pragma unroll
      for (int k = 0; k < FIRST; k++) {
        if (k) { mbar_expect(BAR(B_FULL1 + k), P1_STAGE); tma2d(sb + k * P1_STAGE, &P.x, 64 * k, 128 * rb, BAR(B_FULL1 + k)); }
#pragma unroll
        for (int r = 0; r < 2; r++) {
          tma3d(sb + k * P1_STAGE + 16384 + r * 12288, &P.qkv128, 80 * c, 64 * k + 32 * r, 0, BAR(B_FULL1 + k));
          tma3d(sb + k * P1_STAGE + 40960 + r * 3072, &P.qkv32, 80 * c + 64, 64 * k + 32 * r, 0, BAR(B_FULL1 + k));
          T8(43 + r);
        }
      }
    }
    __syncwarp();
  } else if (warp < 4) {
    if (XST >= 3) ticket();
    if (TW && warp == 2) {
      uint8_t* const a = lane < 2 ? g_kx + (size_t)role * 20480 + 20448 : lane < 4 ? g_x + (size_t)role * X_SIZE + X_G + 27 * 256 : lane < 6 ? g_p + (size_t)role * 20480 + 19 * 256
                         : lane < 8 ? g_kv + (size_t)role * 2 * HB : lane < 10 ? g_xs + role * 1024 : (uint8_t*)&g_cs1[(c * 16 + rb) * 240];
      if (lane < 12 && (TW >> (lane >> 1) & 1)) stx2(a + (lane & 1) * 16, 0);
    }
    if ((TW & 64) && warp == 3 && lane < 5) {
      const uint8_t* const a = lane == 0 ? (const uint8_t*)P.wop + role * 6400 : lane < 3 ? (const uint8_t*)P.w1p + (lane - 1) * 2080000 + role * 1024 : (const uint8_t*)P.w2p + (lane - 3) * 2080000 + role * 1024;
      asm volatile("prefetch.global.L2 [%0];" ::"l"(a) : "memory");
    }
    if (XE) cs_rows();
  } else if (warp >= 4) {
    if (elect()) {
#pragma unroll
      for (int j = 0; j < 4; j++) {
        const int i = 4 + (warp - 4) * 4 + j;
        if (i < B_COUNT && !(XST && XST < 3 && XB == 1 && i == B_ZERO)) mbar_init(BAR(i), KW && i == B_CS ? 2 : i < B_XR ? 1 : i < B_KVW ? 2 : i < B_H1 ? 4 : i < B_EMPTY1 ? 8 : 16);
      }
      asm volatile("fence.mbarrier_init.release.cluster;" ::: "memory");
    }
    __syncwarp();
  }
  __syncthreads();
  asm volatile("barrier.cluster.arrive.relaxed.aligned; barrier.cluster.wait.aligned;" ::: "memory");
  unsigned* const myflag = &g_flag[role * 32];

  if (warp < 4) {
    asm volatile("setmaxnreg.dec.sync.aligned.u32 56;");
    if (warp == 0) {
      if (lane == 0) T8(45);
#pragma unroll 1
      for (int k = PRO ? 1 : FIRST; k < 10; k++) {
        const int s = k & 3;
        if (k >= 4) mbar_wait(BAR(B_EMPTY1 + s), ((k >> 2) - 1) & 1);
        if (PACE1 == 1 && (k & 2) && k < 4) mbar_wait(BAR(B_FULL1 + k - 2), 0);
        if (PACE1 == 2 && k == 2) mbar_wait(BAR(B_FULL1), 0);
        if (PACE1 == 3 && k == 3) mbar_wait(BAR(B_FULL1), 0);
        if (elect()) {
          const uint32_t d = sb + s * P1_STAGE, fb = BAR(B_FULL1 + s);
          const int ks = XST < 4 || c < XC0 || k < XSP || k > c + 2 ? k : k == XSP ? c + 2 : k - 1;
          if (k >= 1) { mbar_expect(fb, P1_STAGE); tma2d(d, &P.x, 64 * ks, 128 * rb, fb); }
          tma3d_mc(d + 16384 + rank * 12288, &P.qkv128, 80 * c, 64 * ks + 32 * rank, 0, fb);
          tma3d_mc(d + 40960 + rank * 3072, &P.qkv32, 80 * c + 64, 64 * ks + 32 * rank, 0, fb);
        }
        __syncwarp();
        if (k < 4 && lane == 0) T8(46 + k);
        if (XPF && k == XPF && lane < 16) bulk_prefetch((const uint8_t*)P.xp + (128 * rb + 16 * c + lane) * 1280 + XPO, 1280 - XPO);
        if (k == 3 && lane < 5) asm volatile("prefetch.tensormap [%0];" ::"l"(&P.wo + lane) : "memory");
      }
      mbar_wait(BAR(B_P1DONE), 0);
      mbar_wait(BAR(B_KVF), 0);
      if (elect()) {
        mbar_expect(BAR(B_WOFULL), 64000);
#pragma unroll
        for (int i = 0; i < 2; i++) tma3d_mc(sb + SM_WO + (2 * i + rank) * 12800, &P.wo, 0, 80 * (2 * i + rank), 5 * c, BAR(B_WOFULL));
        tma3d(sb + SM_WO + 4 * 12800, &P.wo, 0, 320, 5 * c, BAR(B_WOFULL));
      }
      __syncwarp();
      mbar_wait(BAR(B_H1), 0);
      if (elect()) {
        mbar_expect(BAR(B_WOFULL + 1), 38400 + 20480);
        tma2d(sb + SM_XR, &P.xr, 80 * c, 128 * rb, BAR(B_WOFULL + 1));
        for (int j = 5; j < 8; j++) tma3d(sb + SM_WOL + (j - 5) * 12800, &P.wo, 0, 80 * j, 5 * c, BAR(B_WOFULL + 1));
      }
      __syncwarp();
#pragma unroll 1
      for (int n = 0; n < 16; n++) {
        const int s = n % 6;
        const uint32_t d = sb + b_slot(s), fb = BAR(B_BFULL + s);
        mbar_wait(BAR(B_BEMPTY + s), (n / 6) & 1);
        if (n == 0) TSW(18);
        if (n == 2) TSW(22);
        if (n == 3) TSW(24);
        if (n == 6) TSW(25);
        if (n == 8) TSW(26);
        if (n == 13) TSW(16);
        if (elect()) {
          if (n < 8) {
            const int src = PEERX ? c ^ ((2 * n + (n >> 2)) & 7) : n == 0 ? c : (n - 1) + (n - 1 >= c);
            mbar_expect(fb, 35840);
            tma3d_mc(d + rank * 17920, &P.w1, 0, 80 * src + 40 * rank, 7 * c - (BAL5 && c == 7), fb);
          } else {
            const int e = G_ORDER >> (4 * (n - 8)), i = e & 3, j = c >> 1;
            const int src = i == 0 ? c : (((i - 1) + (i - 1 >= j)) << 1) + (c & 1);
            mbar_expect(fb, 35840);
            tma3d_mc(d + rank * 17920, &P.w2, 0, 224 * src - (BAL5 && src == 7 ? 32 : 0) + 112 * ((e >> 2) & 1) + 56 * rank, 5 * j, fb);
          }
        }
        __syncwarp();
      }
    } else {
      const int wq = warp - 1;
      unsigned* const csflag = &g_flag[(128 + c) * 32];
      float* const red = reinterpret_cast<float*>(smem + (XST ? SM_HW : SM_SW));
      const int L = wq * 32 + lane;
      const uint32_t wa = sb + SM_HW + wq * 480 + lane * 16;
      auto prew = [&](unsigned ep) {
        const uint64_t inv = (ep & 1) ^ 1;
#pragma unroll 2
        for (int i = wq; i < (KC || KW ? 0 : 40 - KN); i += 3) stx2(g_kx + (size_t)role * 20480 + i * 512 + lane * 16, inv);
        if (wq) {
          const uint32_t k = lane >> 4, wu = (lane >> 1) & 7;
          const uint32_t o = wq == 1 ? (k ? X_H : X_O) + wu * 2560 + 9 * 256 : X_G + wu * 7168 + (k ? 27 : 13) * 256;
          stx2(g_x + (size_t)role * X_SIZE + o + (lane & 1) * 16, inv);
        }
      };
      auto x_rows = [&]() {
        if (L == 64) { mbar_expect(BAR(B_ZERO), 20480); bulk_g2s(sb + SM_HX, P.xp + (128 * rb + 16 * c) * DM, 20480, BAR(B_ZERO)); }
        __syncwarp();
      };
      uint8_t* const csp = reinterpret_cast<uint8_t*>(&g_cs1[c * 256]);
      if (wq == 0) {
        const unsigned e = __shfl_sync(0xffffffffu, (unsigned)(tk / NCTA) + 1, 31);
        sts32(sb + SM_EP, e);
        if (lane < 4) asm volatile("st.relaxed.gpu.global.v4.b32 [%0], {%1,%1,%1,%1};" ::"l"(csp + rb * 64 + lane * 16), "r"((e & 1) ^ 1) : "memory");
        if (XSW) {
#pragma unroll
          for (int i = 0; i < 2; i++) asm volatile("st.relaxed.gpu.global.v4.b32 [%0], {%1,%1,%1,%1};" ::"l"(g_xs + role * 1024 + i * 512 + lane * 16), "r"((e & 1) ^ 1) : "memory");
        }
        __syncwarp();
        if (lane == 0) mbar_arrive(BAR(B_ZERO));
        if (lane == 0) T8(59);
      }
      mbar_wait(BAR(B_FULL1 + XD - 1), 0);
      const uint32_t wb = sb + SM_HW + L * 16;
      {
        const int j = min(rb, 14);
        const __nv_bfloat16* src = P.wqkvp + (size_t)(L >> 1) * (3 * DM) + (j / 5) * DM + 80 * c + (j % 5) * 16 + (L & 1) * 8;
#pragma unroll 1
        for (int i = wq ? 1 : 0; i < 14; i++) cp16(wb + (13 - i) * 1536, src + (13 - i) * (48 * 3 * DM));
      }
      asm volatile("cp.async.commit_group;" ::: "memory");
      if (XP == 4) { mbar_wait(BAR(B_ZERO), 0); prew(lds32(sb + SM_EP)); }
      asm volatile("cp.async.wait_group 0;" ::: "memory");
      float csa[8] = {0.f, 0.f, 0.f, 0.f, 0.f, 0.f, 0.f, 0.f};
#pragma unroll 1
      for (int b = 0; b < 2; b++) {
        uint4 wv[7];
#pragma unroll
        for (int i = 0; i < 7; i++) wv[i] = lds128(wb + (7 * b + i) * 1536);
#pragma unroll
        for (int i = 0; i < 7; i++) if (i < 6 || !(b && wq)) acc8(csa, wv[i]);
      }
      if (lane == 0 && wq < 2) T8(55 + wq);
#pragma unroll
      for (int n = 4; n >= 1; n >>= 1) {
        const bool h = lane & (4 * n);
#pragma unroll
        for (int i = 0; i < n; i++) csa[i] = (h ? csa[i + n] : csa[i]) + __shfl_xor_sync(0xffffffffu, h ? csa[i] : csa[i + n], 4 * n);
      }
      csa[0] += __shfl_xor_sync(0xffffffffu, csa[0], 2);
      float* const red2 = reinterpret_cast<float*>(smem + SM_CS2);
      red2[wq * 16 + (lane & 1) * 8 + (lane >> 2)] = csa[0];
      asm volatile("bar.sync 2, 96;" ::: "memory");
      const unsigned ep = lds32(sb + SM_EP);
      if (L < 16) asm volatile("st.relaxed.gpu.global.b32 [%0], %1;" ::"l"(csp + rb * 64 + L * 4), "r"(tag(__float_as_uint(red2[L] + red2[16 + L] + red2[32 + L]), ep & 1)) : "memory");
      if (L == 0) T8(57);
      if (XP == 0) prew(ep);
      if (wq < 2) {
        uint32_t v[4], n = 0;
        do ldx2(v, csp + min(L, 59) * 16);
        while (__any_sync(0xffffffffu, (((v[0] ^ ep) | (v[1] ^ ep) | (v[2] ^ ep) | (v[3] ^ ep)) & 1)) && ++n < SPIN_LIMIT);
        if (L < 60) *reinterpret_cast<uint4*>(smem + SM_CS1 + L * 16) = make_uint4(v[0], v[1], v[2], v[3]);
      }
      if (L == 0) T8(58);
      if (XP == 7) {
        asm volatile("bar.sync 2, 96;" ::: "memory");
        if (L == 0) mbar_arrive(BAR(B_CS));
      }
      if (XP >= 6) mbar_wait(BAR(B_FULL1 + (XPK & 3)), (XPK >> 2) & 1);
      if (XP >= 5) prew(ep);
      asm volatile("bar.sync 2, 96;" ::: "memory");
      if (L == 0) mbar_arrive(BAR(XP == 7 ? B_ZERO : B_CS));
      if (L == 0) T8(51);
      if (PPW == 4 && wq) {
        uint8_t* const dst = g_p + (size_t)role * 20480 + (wq - 1) * 10240 + lane * 16;
#pragma unroll 4
        for (int i = 0; i < 20; i++) stx2(dst + i * 512, (uint64_t)((ep & 1) ^ 1));
      }
      if (wq == 0) {
        const int j = lane & 3, hf = 1 - (j & 1), srb = rb - 1 - (j >> 1), sr = max(srb, 0) * 8 + c;
        const unsigned* const fl = &g_flag[sr * 32 + F_KV + hf];
        if (lane == 0) mbar_expect(BAR(B_KVF), 4 * HB);
        const uint8_t* const ksrc = srb >= 0 ? g_kv + (size_t)(sr * 2 + hf) * HB : g_none;
        mbar_wait(BAR(B_P1DONE), 0);
        bool todo = lane < 4;
#pragma unroll 1
        for (uint32_t n = 0; __any_sync(0xffffffffu, todo) && n < SPIN_LIMIT; n++) {
          if (todo && (srb < 0 || (int)(ld_rlx(fl) - ep) >= 0)) {
            fence_async();
            bulk_g2s(sb + SM_KV1 + (2 + (EARLY0 && j < 2 ? j ^ 1 : j)) * HB, ksrc, HB, BAR(B_KVF));
            todo = false;
          }
          __syncwarp();
        }
        TSW(33);
      } else {
        const int hf = wq - 1;
        mbar_wait(BAR(B_KVW + hf), 0);
        if (elect()) {
          fence_async_smem();
          asm volatile("cp.async.bulk.global.shared::cta.bulk_group [%0], [%1], %2;"
                       ::"l"(g_kv + (size_t)(role * 2 + hf) * HB), "r"(sb + SM_KV1 + (1 - hf) * HB), "r"(HB) : "memory");
          asm volatile("cp.async.bulk.commit_group;" ::: "memory");
          asm volatile("cp.async.bulk.wait_group 0;" ::: "memory");
          mbar_wait(BAR(B_KVW + 2 + hf), 0);
          flag_set(myflag + F_KV + hf, ep);
        }
        __syncwarp();
        mbar_wait(BAR(B_KVF), 0);
        if (hf == 0) TBW(60);
        {
          uint8_t* const dst = g_p + (size_t)role * 20480 + hf * 10240 + lane * 16;
          if (PPW == 1) {
#pragma unroll 4
            for (int i = 0; i < 20; i++) stx2(dst + i * 512, (uint64_t)((ep & 1) ^ 1));
          }
          if (PPW == 2 && lane < 4) stx2(g_p + (size_t)role * 20480 + (2 * hf + (lane >> 1)) * 5120 + 19 * 256 + (lane & 1) * 16, (uint64_t)((ep & 1) ^ 1));
          if (PREW & 6) {
            uint8_t* const gx = g_x + (size_t)role * X_SIZE + lane * 16;
            const uint64_t inv = (ep & 1) ^ 1;
            if (PREW & 2) {
#pragma unroll 4
              for (int i = hf; i < 42; i += 2) stx2(gx + X_H + i * 512, inv);
            }
            if (PREW & 4) {
#pragma unroll 4
              for (int i = hf; i < 112; i += 2) stx2(gx + X_G + i * 512, inv);
            }
          }
          TBW(62 + hf);
          asm volatile("bar.sync 13, 64;" ::: "memory");
          if (hf == 0) TSW(34);
        }
        if (PPW == 5) {
          mbar_wait(BAR(B_WOFULL + 1), 0);
          uint8_t* const dst = g_p + (size_t)role * 20480 + hf * 10240 + lane * 16;
#pragma unroll 4
          for (int i = 0; i < 20; i++) stx2(dst + i * 512, (uint64_t)((ep & 1) ^ 1));
          asm volatile("bar.sync 13, 64;" ::: "memory");
        }
        if (hf) {
          poll_flag(&g_flag[136 * 32], 4 * ep);
          for (int L2 = lane; L2 < 56; L2 += 32) *reinterpret_cast<float4*>(smem + SM_CS2 + L2 * 16) = ldcg128f(&g_cs2[c * 224 - (BAL5 && c == 7 ? 32 : 0) + 4 * L2]);
          __syncwarp();
          if (lane == 0) mbar_arrive(BAR(B_CS + 1));
        }
      }
    }
  } else {
    asm volatile("setmaxnreg.inc.sync.aligned.u32 224;");
    pad<PAD0>(P.never);
    const int w = (warp >> 2) - 1, u = ROWX ? (warp - 4) ^ ((c & 1) << 2) : warp - 4, wr = u >> 2, v = warp & 3, g = lane >> 2, t = lane & 3;
    auto release2 = [&](int b) { if (lane == 0) { mbar_arrive_cta(BAR(b), 0); mbar_arrive_cta(BAR(b), 1); } };
    auto release1 = [&](int b) { if (lane == 0) mbar_arrive(BAR(b)); };
    uint32_t zero; asm volatile("mov.u32 %0, 0;" : "=r"(zero));
    uint32_t par = 0, hbits = 0;
    {
      float acc[96], acs[24];
      uint32_t af[2][16];
      float sx0 = 0.f, sq0 = 0.f, sx1 = 0.f, sq1 = 0.f;
      reg_def<96>(acc); reg_def<24>(acs);
      const uint32_t arow = (16 * u + (lane & 15)) * 128, asw = ((lane >> 4) ^ (lane & 7)) << 4;
      TS(0);
      if (w) asm volatile("bar.arrive 11, 256;" ::: "memory");
      uint32_t xs[XST == 5 ? 32 : 8];
#pragma unroll
      for (int i = 0; i < (XST == 5 ? 32 : 8); i++) asm volatile("" : "=r"(xs[i]));
      const uint8_t* xsp = XST == 5 ? g_xs + rb * 32768 + u * 512 + lane * 16 : g_xs + rb * 8192 + t * 2048 + u * 128 + g * 16;
      if (XPIN) asm volatile("" : "+l"(xsp));
      float cse[20];
      if (CSE) reg_def<20>(cse);
#pragma unroll 1
      for (int k2 = 0; k2 < 10; k2 += 2) {
#pragma unroll
        for (int b = 0; b < 2; b++) {
          const int k = k2 + b, s = k & 3;
          const uint32_t d = sb + s * P1_STAGE;
          const uint64_t db = mkdesc(d + 16384, 4096, 1024, 1), dc = mkdesc(d + 40960, 1024, 256, 3);
          mbar_wait(BAR(B_FULL1 + s), (k >> 2) & 1);
          if (k == 0) TS(1);
#pragma unroll
          for (int kk = 0; kk < 4; kk++) ldsm4(&af[b][4 * kk], d + arow + (asw ^ (kk << 5)));
          if (XL4 >= 60 && b == 0 && k2 == XL4 / 10) {
#pragma unroll
            for (int i = 0; i < (XST == 5 ? 8 : 2); i++) ldx2(xs + 4 * i, xsp + (XST == 5 ? 4096 : 1024) * i);
          }
          if (CSE == 1 && b == 1 && k2 == 8) {
            mbar_wait(BAR(B_CS), 0);
#pragma unroll
            for (int j = 0; j < 10; j++) { const float2 y = lds64f(sb + SM_CS1 + 8 * t + ((1 + j / 5) * 80 + (j % 5) * 8) * 4); cse[2 * j] = y.x; cse[2 * j + 1] = y.y; }
          }
          reg_fence<96>(acc); reg_fence<24>(acs);
          asm volatile("bar.sync %0, 256;" ::"r"(11 + w) : "memory");
          wg_fence();
#pragma unroll
          for (int kk = 0; kk < 4; kk++) {
            const int sd = kk || b || k2;
            wg_rs<48, 1>(acs, &af[b][4 * kk], dc + (kk >> 1) * 192 + (kk & 1) * 32, sd);
            wg_rs<192, 1>(acc, &af[b][4 * kk], db + (kk >> 1) * 768 + (kk & 1) * 128, sd);
          }
          wg_commit();
          if (ORD1 != 3 && !(w && k == 9)) asm volatile("bar.arrive %0, 256;" ::"r"(12 - w) : "memory");
          if (XST < 3) bb(P.never);
          if (b == 1 && k2 == 0) { mbar_wait(BAR(B_ZERO), 0); par = lds32(sb + SM_EP + (lane & P.never)) & 1; }
          if (b == (XL4 & 1) && k2 == (XL4 & ~1)) {
#pragma unroll
            for (int i = 0; i < (XST == 5 ? 8 : 2); i++) ldx2(xs + 4 * i, xsp + (XST == 5 ? 4096 : 1024) * i);
          }
          if (b == (XF4 & 1) && k2 == (XF4 & ~1)) {
            if (XST == 5) x_chkU(xs, xsp, par); else x_chkV(xs, xsp, par);
            float a[4];
#pragma unroll
            for (int i = 0; i < 4; i++) {
              const float* const y = reinterpret_cast<const float*>(xs) + i;
              a[i] = XST == 5 ? ((y[0] + y[4]) + (y[8] + y[12])) + ((y[16] + y[20]) + (y[24] + y[28])) : y[0] + y[4];
            }
            sx0 = a[0]; sq0 = a[1]; sx1 = a[2]; sq1 = a[3];
#pragma unroll
            for (int i = 0; i < 4; i++) xs[i] = __shfl_xor_sync(0xffffffffu, __float_as_uint(a[i]), 1);
          }
          if (b == ((XF4 + 1) & 1) && k2 == ((XF4 + 1) & ~1)) {
            if (CSE == 2) {
              mbar_wait(BAR(B_CS), 0);
#pragma unroll
              for (int j = 0; j < 10; j++) { const float2 y = lds64f(sb + SM_CS1 + 8 * t + ((1 + j / 5) * 80 + (j % 5) * 8) * 4); cse[2 * j] = y.x; cse[2 * j + 1] = y.y; }
            }
            float a[4] = {sx0, sq0, sx1, sq1};
#pragma unroll
            for (int i = 0; i < 4; i++) { a[i] += __uint_as_float(xs[i]); a[i] = (a[i] + __shfl_xor_sync(0xffffffffu, a[i], 2)) * (1.f / DM); }
            sq0 = rsq_a(fmaxf(a[1] - a[0] * a[0], 0.f) + 1e-5f); sq1 = rsq_a(fmaxf(a[3] - a[2] * a[2], 0.f) + 1e-5f);
            sx0 = -a[0] * sq0; sx1 = -a[2] * sq1;
          }
          if (XST == 3 ? k == c || k2 == 8 : k == (c < XC0 ? c + 2 : XSP) || k == c - 6)
#pragma unroll
          for (int i = 0; i < 16; i += 2) {
            const float x0 = bf_lo(af[b][i]), x1 = bf_hi(af[b][i]), y0 = bf_lo(af[b][i + 1]), y1 = bf_hi(af[b][i + 1]);
            sx0 += x0 + x1; sq0 = fmaf(x0, x0, fmaf(x1, x1, sq0)); sx1 += y0 + y1; sq1 = fmaf(y0, y0, fmaf(y1, y1, sq1));
          }
          asm volatile("" : "+f"(sx0), "+f"(sq0), "+f"(sx1), "+f"(sq1));
          if (k == (c < XC0 ? c + 2 : XSP)) {
            const bool h2 = t & 2, h1 = t & 1;
            const float y0 = (h2 ? sx1 : sx0) + __shfl_xor_sync(0xffffffffu, h2 ? sx0 : sx1, 2), y1 = (h2 ? sq1 : sq0) + __shfl_xor_sync(0xffffffffu, h2 ? sq0 : sq1, 2);
            const float y = (h1 ? y1 : y0) + __shfl_xor_sync(0xffffffffu, h1 ? y0 : y1, 1);
            asm volatile("st.relaxed.gpu.global.b32 [%0], %1;" ::"l"(xsp + (c * 1024 - t * 2044)), "r"(tag(__float_as_uint(y), par)) : "memory");
          }
          wg_wait<1 + QSPLIT>();
          reg_fence_u<16>(af[b ^ 1]);
          if (k >= 1 && k <= 6) release2(B_EMPTY1 + ((k - 1) & 3));
          if (w && k == 8) asm volatile("bar.arrive 15, 256;" ::: "memory");
        }
      }
      const float n0s = sx0, r0s = sq0, n1s = sx1, r1s = sq1;
      if (!CSE) mbar_wait(BAR(B_CS), 0);
      if (XP == 7) mbar_wait(BAR(B_ZERO), 1);
      uint32_t csa = sb + SM_CS1 + 8 * t;
      asm volatile("" : "+r"(csa)::"memory");
      TS(14);
      uint8_t* const kxw = g_kx + (size_t)role * 20480 + u * 2560 + lane * 8;
      const uint32_t kvst = sb + SM_KV0 + (1 - wr) * HB + (lane >> 4) * 1024 + (2 * v + ((lane >> 3) & 1)) * 128 + (lane & 7) * 16;
      auto lnoff = [&](int m, int j, float* o, float n0, float n1) {
        const float2 cs = lds64c(csa + (m * 80 + j * 8) * 4);
        o[0] = n0 * cs.x; o[1] = n0 * cs.y; o[2] = n1 * cs.x; o[3] = n1 * cs.y;
      };
      auto lnq = [&](int m, int j, uint32_t* r, const float* o, float r0s, float r1s) {
        const float* a = j < 8 ? &acc[m * 32 + j * 4] : &acs[m * 8 + (j - 8) * 4];
        r[0] = pack2(fmaf(a[0], r0s, o[0]), fmaf(a[1], r0s, o[1]));
        r[1] = pack2(fmaf(a[2], r1s, o[2]), fmaf(a[3], r1s, o[3]));
      };
      const bool lo = t < 2;
      auto store_kv = [&](uint32_t a, const uint32_t* r, uint32_t one) {
#pragma unroll
        for (int j = 0; j < 6; j += 2) stsm4(a + j * 1024, r[2 * j], r[2 * j + 1], r[2 * j + 2], r[2 * j + 3]);
        stsm4(a + 6144, r[12], r[13], lo ? r[14] : one, lo ? r[15] : one);
        stsm4(a + 8192, lo ? one : r[14], lo ? one : r[15], r[16], r[17]);
        stsm2(a + 10240, r[18], r[19]);
      };
      if (!w) asm volatile("bar.sync 15, 256;" ::: "memory");
      float off0[10][4];
#pragma unroll
      for (int j = 0; j < 10; j++) { off0[j][0] = n0s * cse[2 * j]; off0[j][1] = n0s * cse[2 * j + 1]; off0[j][2] = n1s * cse[2 * j]; off0[j][3] = n1s * cse[2 * j + 1]; }
      reg_fence<40>(off0[0]);
      bb(P.never);
      wg_wait<QSPLIT>();
      reg_fence<64>(acc + 32); reg_fence<24>(acs);
      TS(2); TS1(17);
#pragma unroll
      for (int p = 0; p < 2; p++) {
        uint32_t r[10][2];
#pragma unroll
        for (int j = 0; j < 10; j++) {
          if (p) lnoff(1 + j / 5, 5 + j % 5, off0[j], n0s, n1s);
          lnq(1 + j / 5, 5 * p + j % 5, r[j], off0[j], r0s, r1s);
          if (p == 0) { r[j][0] = KC ? r[j][0] | 1 : tag(r[j][0], par); stx(kxw + j * 256, r[j][0], r[j][1]); }
        }
        if (p == 0) {
          TS(15); TS1(18);
          wg_wait<0>();
          reg_fence<32>(acc); reg_fence_u<32>(&af[0][0]);
          release2(B_P1DONE);
        }
        store_kv(kvst - p * (SM_KV0 - SM_KV1), r[0], 0x3f803f80u);
        TS(16 + p);
      }
      if (KVE == 1) { __syncwarp(); release1(B_KVW + wr); }
      uint32_t kr[2][20];
      const uint8_t* const kx0 = g_kx + (size_t)(max(rb - 1, 0) * 8 + c) * 20480 + u * 2560 + lane * 8;
      const uint8_t* const kx1 = g_kx + (size_t)(max(rb - 2, 0) * 8 + c) * 20480 + u * 2560 + lane * 8;
      if (LPOS == 0) { mbar_wait(BAR(B_P1DONE), 0); x_load<10, 256>(kr[0], kx0); x_load<10, 256>(kr[1], kx1); }
      if (LPOS == 3) { if (w) mbar_wait(BAR(B_P1DONE), 0); x_load<10, 256>(kr[0], kx0); x_load<10, 256>(kr[1], kx1); }
      if (LPOS == 4) { bb(P.never); x_load<10, 256>(kr[0], kx0); x_load<10, 256>(kr[1], kx1); }
      TS(18);
      uint32_t q[10][2];
#pragma unroll
      for (int j = 0; j < 10; j++) { lnoff(0, j, off0[j], n0s * SM_C, n1s * SM_C); lnq(0, j, q[j], off0[j], r0s * SM_C, r1s * SM_C); }
      reg_fence_u<20>(q[0]);
      if (FEWV != 3) TS(32);
      if (KVE == 2) { __syncwarp(); release1(B_KVW + wr); }
      mbar_wait(BAR(B_P1DONE), 0);
      if (LPOS == 1) { x_load<10, 256>(kr[0], kx0); x_load<10, 256>(kr[1], kx1); }
      const uint32_t qst = kvst - (SM_KV0 + HB - SM_Q) + wr * (12288 + HB);
#pragma unroll
      for (int p = 0; p < 2; p++) {
        const uint32_t(*r)[2] = q + 5 * p;
        stsm4(qst + p * 6144, r[0][0], r[0][1], r[1][0], r[1][1]);
        stsm4(qst + p * 6144 + 2048, lo ? r[2][0] : zero, lo ? r[2][1] : zero, lo ? zero : r[2][0], lo ? zero : r[2][1]);
        stsm4(qst + p * 6144 + 4096, r[3][0], r[3][1], r[4][0], r[4][1]);
      }
      if (!EARLY0) sts32(sb + SM_QZ + (threadIdx.x - 128) * 4, zero);
      else if (!w) asm volatile("st.shared.v2.u32 [%0], {%1,%1};" ::"r"(sb + SM_QZ + (threadIdx.x - 128) * 8), "r"(zero) : "memory");
      if (LPOS == 2) { mbar_wait(BAR(B_P1DONE), 0); x_load<10, 256>(kr[0], kx0); x_load<10, 256>(kr[1], kx1); }
      TS(5); TS1(22);
#pragma unroll
      for (int m = 0; m < 2; m++) {
        x_chk10(kr[m], m ? kx1 : kx0, KC ? 1 : par);
        if (rb <= m) {
#pragma unroll
          for (int j = 0; j < 20; j++) kr[m][j] = zero;
          reg_fence_u<20>(kr[m]);
        }
        store_kv(kvst + (2 + 2 * m) * HB + (EARLY0 && m == 0 ? (2 * wr - 1) * (int)HB : 0), kr[m], rb <= m ? 0u : 0x3f803f80u);
      }
      if (KVE == 0) release1(B_KVW + wr);
      release1(B_KVW + 2 + wr);
      TB(61); TS1(24);
      fence_async_smem();
      if (w) { asm volatile("bar.arrive 10, 256;" ::: "memory"); asm volatile("bar.sync 1, 256;" ::: "memory"); }
      else { asm volatile("bar.arrive 1, 256;" ::: "memory"); asm volatile("bar.sync 7, 128;" ::: "memory"); }
      TS(3);
    }
    uint32_t oa[2][32], ob[32];
    bool wf0, wf1;
    uint8_t* xo = g_x + (size_t)rb * 8 * X_SIZE + X_O + u * 2560 + lane * 8;
    asm volatile("" : "+l"(xo));
    pad<PADA>(P.never);
    {
      const uint32_t tri0 = 2 * t <= g ? 0xffffffffu : 0u, tri1 = 2 * t + 1 <= g ? 0xffffffffu : 0u, tri = (tri0 & 0xffffu) | (tri1 & 0xffff0000u);
      const uint32_t sb4 = (sb >> 4) & 0x3FFF;
      struct Unit { uint64_t k0, k1, q0, q1, v; };
      auto unit = [&](int it) {
        const uint32_t odd = it & 1, pr = (it >> 1) & 1;
        const uint32_t kb = sb4 + (SM_KV0 + HB >> 4) - wr * (HB >> 4) - pr * (SM_KV0 - SM_KV1 >> 4), qb = sb4 + (SM_Q >> 4) + wr * 768 + pr * 384, qh = qb + 128 + odd * 64;
        const uint64_t hs = (uint64_t)8 << 32;
        Unit n;
        n.k0 = hs | (64 << 16) + kb + odd * 192; n.k1 = hs | (64 << 16) + kb + 128;
        n.q0 = hs | (64 << 16) + qb + odd * 256; n.q1 = hs | (sb4 + (SM_QZ >> 4) - qh << 16) + qh;
        n.v = (uint64_t)64 << 32 | (8 << 16) + kb + odd * 192 + 320;
        return n;
      };
      float o[24], s[5][32];
      uint32_t bad = 0;
      uint8_t* const go = xo + c * X_SIZE;
      auto store_o = [&](int it, auto second) {
        const bool odd = it & 1;
        float a[12];
#pragma unroll
        for (int j = 0; j < 12; j++) a[j] = o[j] + o[j + 12];
        const int src = (lane & 28) + (odd ? 0 : 2);
        const float l0 = __shfl_sync(0xffffffffu, odd ? a[0] : a[8], src), l1 = __shfl_sync(0xffffffffu, odd ? a[2] : a[10], src);
        const float i0 = rcp_a(l0), i1 = rcp_a(l1);
        if constexpr (!second.value) { if (!(fminf(l0, l1) >= 0x1p-30f && l0 + l1 <= 0x1p30f)) bad |= 2u << it; }
        uint8_t* const gp = go + ((it >> 1) * 5 + (it & 1) * 2) * 256;
        const bool mine = (((bad >> (it + 1)) & 1) != 0) == second.value;
        uint32_t r[3][2];
#pragma unroll
        for (int j = 0; j < 3; j++) {
          r[j][0] = tag(pack2(a[4 * j] * i0, a[4 * j + 1] * i0), par);
          r[j][1] = pack2(a[4 * j + 2] * i1, a[4 * j + 3] * i1);
        }
        stxp(gp, r[0][0], r[0][1], mine && !(odd && t < 2));
        stxp(gp + 256, r[1][0], r[1][1], mine);
        stxp(gp + 512, r[2][0], r[2][1], mine && (odd || t < 2));
      };
      auto pair0_done = [&](uint32_t veto, bool now) {
        asm volatile("{.reg .pred p; setp.ne.u32 p, %1, 0; vote.sync.any.pred p, p, 0xffffffff; setp.ne.and.u32 p, %2, 0, !p; @p mbarrier.arrive.shared::cta.b64 _, [%0];}"
                     ::"r"(BAR(B_H1)), "r"(veto), "r"((uint32_t)(now && lane == 0)) : "memory");
      };
      uint32_t mk0[4], mk1[4], mkp[4], mle[4];
#pragma unroll
      for (int q = 0; q < 4; q++) {
        mk0[q] = q < v ? 0xffffffffu : q == v ? tri0 : 0u; mk1[q] = q < v ? 0xffffffffu : q == v ? tri1 : 0u;
        mkp[q] = q < v ? 0xffffffffu : q == v ? tri : 0u; mle[q] = q <= v ? 0xffffffffu : 0u;
      }
      reg_fence_u<4>(mk0); reg_fence_u<4>(mk1); reg_fence_u<4>(mkp); reg_fence_u<3>(mle + 1);
      auto merge = [&]() {
#pragma unroll
        for (int q = 0; q < 4; q++) {
#pragma unroll
          for (int e = 0; e < 8; e++) {
            if ((e == 2 || e == 3) && q == 0) continue;
            const uint32_t mk = (e == 2 || e == 3) ? mle[q] : (e == 4 || e == 5) ? (q == 3 ? zero : mle[q + 1]) : (e & 1) ? mk1[q] : mk0[q];
            asm("lop3.b32 %0, %0, %1, %2, 0xE4;" : "+f"(s[0][8 * q + e]) : "f"(s[4][8 * q + e]), "r"(mk));
          }
        }
      };
      auto split = [&](uint32_t* pd, uint32_t* pt) {
#pragma unroll
        for (int q = 0; q < 4; q++) {
          pt[4 * q] = pd[4 * q] & ~mkp[q]; pd[4 * q] &= mkp[q];
          pt[4 * q + 3] = pd[4 * q + 3] & ~mkp[q]; pd[4 * q + 3] &= mkp[q];
          pt[4 * q + 1] = q == 0 ? zero : pd[4 * q + 1] & ~mle[q]; if (q) pd[4 * q + 1] &= mle[q];
          pt[4 * q + 2] = q == 3 ? pd[4 * q + 2] : pd[4 * q + 2] & ~mle[q + 1]; pd[4 * q + 2] = q == 3 ? zero : pd[4 * q + 2] & mle[q + 1];
        }
        reg_fence_u<16>(pd); reg_fence_u<16>(pt);
      };
      auto qk = [&](int i, const Unit& n, int part) {
        if (part == 0) wgmma_sz_n64<0>(s[i], n.q0, n.k0 + i * (HB >> 4));
        else wg_ss<64, 0>(s[i], n.q1, n.k1 + i * (HB >> 4), 1);
      };
      auto dv = [&](int i, const Unit& n) { return n.v + i * (HB >> 4); };
      TS(27);
      Unit h = unit(0);
      wg_fence();
      qk(0, h, 0); qk(4, h, 0); qk(1, h, 0); qk(0, h, 1); qk(4, h, 1); qk(1, h, 1);
      wg_commit();
      if (w && STAGP != 3) asm volatile("bar.sync %0, 64;" ::"r"(3 + v) : "memory");
      wg_wait<0>();
      reg_fence<64>(s[0]); reg_fence<32>(s[4]);
      merge();
      bad = 1;
      reg_def<24>(o);
      uint32_t p[4][16], pt[16];
#pragma unroll
      for (int i = 0; i < 16; i++) p[3][i] = zero;
      attn_pre<E0A>(s[0]);
#pragma unroll 1
      for (int it = 0;; it++) {
        const Unit hn = unit(it + 1);
        wg_wait<0>();
        reg_fence<24>(o); reg_fence_u<16>(p[3]);
        store_o(it - 1, BoolC<false>());
        pair0_done(bad >> 1, it == 2);
        if (FEWV == 2 && it == 2) TS(63);
        attn_exp<0, 16, E0A>(s[0], p[0]);
        split(p[0], pt);
        if (STAGP == 2 && !w && it == STAGU) asm volatile("bar.arrive %0, 64;" ::"r"(3 + v) : "memory");
        if (EARLY0 == 1 && !w && it == 0) asm volatile("bar.sync 10, 256;" ::: "memory");
        wg_fence();
        if (EARLY0 == 2) { if (w || it) { qk(2, h, 0); qk(3, h, 0); qk(2, h, 1); qk(3, h, 1); } }
        attn_pv0(o, p[0], pt, dv(0, h), dv(4, h));
        if (EARLY0 != 2) { qk(2, h, 0); qk(3, h, 0); qk(2, h, 1); qk(3, h, 1); }
        wg_commit();
        attn_exp<0, 16, 0>(s[1], p[1]);
        if (STAGP == 0 && !w && it == STAGU) asm volatile("bar.arrive %0, 64;" ::"r"(3 + v) : "memory");
        if (EARLY0 == 2 && !w && it == 0) {
          asm volatile("bar.sync 10, 256;" ::: "memory");
          wg_fence();
          qk(2, h, 0); qk(3, h, 0); qk(2, h, 1); qk(3, h, 1);
          wg_commit();
        }
        wg_wait<0>();
        reg_fence<64>(s[2]); reg_fence_u<16>(p[0]); reg_fence_u<16>(pt);
        wg_fence();
        attn_pv(o, p[1], dv(1, h));
        wg_commit();
        attn_exp<0, E2A, 0>(s[2], p[2]);
        if (it == 3) break;
        if (it == 1) mbar_wait(BAR(B_KVF), 0);
        attn_exp<E2A, 16, 0>(s[2], p[2]);
        wg_wait<0>();
        reg_fence_u<16>(p[1]);
        wg_fence();
        attn_pv(o, p[2], dv(2, h));
        qk(0, hn, 0); qk(4, hn, 0); qk(1, hn, 0); qk(0, hn, 1); qk(4, hn, 1); qk(1, hn, 1);
        wg_commit();
        attn_exp<0, 16, 0>(s[3], p[3]);
        wg_wait<0>();
        reg_fence<64>(s[0]); reg_fence<32>(s[4]); reg_fence_u<16>(p[2]);
        wg_fence();
        attn_pv(o, p[3], dv(3, h));
        wg_commit();
        merge();
        attn_pre<E0A>(s[0]);
        if (FEWV != 3) TS(28 + it);
        h = hn;
      }
      auto after = [&](uint32_t x) { return xo + (x & P.never); };
#pragma unroll
      for (int i = 0; i < 8; i++) x_load<4, 256>(&oa[i >> 2][8 * (i & 3)], xo + i * X_SIZE);
      wf0 = mbar_test(BAR(B_WOFULL), 0);
      attn_exp<E2A, 16, 0>(s[2], p[2]);
      wg_wait<0>();
      reg_fence_u<16>(p[1]);
      wg_fence();
      attn_pv(o, p[2], dv(2, h));
      wg_commit();
      attn_exp<0, 16, 0>(s[3], p[3]);
      wg_fence();
      attn_pv(o, p[3], dv(3, h));
      wg_commit();
#pragma unroll
      for (int i = 0; i < 8; i++) x_load<2, 256>(&ob[4 * i], xo + i * X_SIZE + 1024);
      wf1 = mbar_test(BAR(B_WOFULL + 1), 0);
      if (FEWV != 3) TS(31);
      wg_wait<0>();
      reg_fence<24>(o); reg_fence_u<32>(p[2]);
      store_o(3, BoolC<false>());
      bad &= ~1u;
      uint32_t redo;
      float mx0, mx1;
      asm volatile("{.reg .pred p, q; setp.ne.u32 p, %1, 0; barrier.cta.red.or.pred.aligned q, %2, 128, p; selp.u32 %0, 1, 0, q;}" : "=r"(redo) : "r"(bad), "r"(7 + w) : "memory");
      if (redo && !NOREDO) {
#pragma unroll 1
        for (int hp = 0; hp < 8; hp++) {
          const Unit hu = unit(hp >> 1);
          const int nch = min(5, 2 * rb + wr + 1);
          const float ninf = -INFINITY;
          if (!(hp & 1)) { mx0 = 0.f; mx1 = 0.f; }
          float m0 = ninf, m1 = ninf;
#pragma unroll 1
          for (int i = 0; i < nch; i++) {
            h = hu;
            h.k0 += i * (HB >> 4); h.k1 += i * (HB >> 4); h.v += i * (HB >> 4);
            wg_fence();
            qk(0, h, 0); qk(0, h, 1);
            wg_commit();
            wg_wait<0>();
            reg_fence<32>(s[0]);
            const int r = 16 * v + g, lo0 = i == 4 ? r + 1 : 0, lo1 = i == 4 ? r + 9 : 0, hi0 = i == 0 ? r : 63, hi1 = i == 0 ? r + 8 : 63;
#pragma unroll
            for (int e = 0; e < 32; e++) {
              const int col = 8 * (e >> 2) + 2 * t + (e & 1);
              const float x = ((e & 2) ? col >= lo1 && col <= hi1 : col >= lo0 && col <= hi0) ? s[0][e] : ninf;
              if (e & 2) m1 = fmaxf(m1, x); else m0 = fmaxf(m0, x);
              s[0][e] = x - ((e & 2) ? mx1 : mx0);
            }
            attn_exp<0, 16, 0>(s[0], p[0]);
            wg_fence();
#pragma unroll
            for (int j = 0; j < 4; j++) wg_rs<24, 1>(o + 12 * (j & 1), p[0] + 4 * j, dv(0, h) + 16 * j, j > 1 || i);
            wg_commit();
            wg_wait<0>();
            reg_fence<24>(o); reg_fence_u<16>(p[0]);
          }
          m0 = fmaxf(m0, __shfl_xor_sync(0xffffffffu, m0, 1)); m1 = fmaxf(m1, __shfl_xor_sync(0xffffffffu, m1, 1));
          mx0 = fmaxf(m0, __shfl_xor_sync(0xffffffffu, m0, 2)); mx1 = fmaxf(m1, __shfl_xor_sync(0xffffffffu, m1, 2));
          if (hp & 1) store_o(hp >> 1, BoolC<true>());
        }
        if (__any_sync(0xffffffffu, bad & 6)) release1(B_H1);
      }
      TS(4);
    }
    auto peer = [&](int i) { return PEERX ? c ^ ((2 * i + (i >> 2)) & 7) : i == 0 ? c : (i - 1) + (i - 1 >= c); };
    uint32_t f[4][28];
    uint32_t* const fa = f[0]; uint32_t* const fb = f[1];
    {
      float acc[40];
      uint32_t ol[2][32];
      if (REL < 2) release2(B_BEMPTY);
      if (REL < 1) release2(B_BEMPTY + 1);
      const uint64_t dw = mkdesc(sb + SM_WO, 2560, 256, 3);
      auto wo_off = [](int i) { return i < 5 ? i * 800 : (SM_WOL >> 4) + (i - 5) * 800; };
      if (FEWV != 3) TS(35);
      const uint8_t* const po = xo - lane * 8 + (lane & 7) * X_SIZE + 9 * 256;
      if (WOS) { if (!wf0) mbar_wait(BAR(B_WOFULL), 0); }
      else if (!(wf0 && wf1)) { mbar_wait(BAR(B_WOFULL), 0); mbar_wait(BAR(B_WOFULL + 1), 0); }
      TB(58);
      const uint32_t xra = sb + SM_XR + (16 * u + (lane & 15)) * 160 + (lane >> 4) * 16;
#pragma unroll
      for (int j = 0; j < 10; j += 2) {
        uint32_t x[4];
        ldsm4(x, xra + j * 16);
#pragma unroll
        for (int i = 0; i < 4; i++) { acc[4 * j + 2 * i] = bf_lo(x[i]); acc[4 * j + 2 * i + 1] = bf_hi(x[i]); }
      }
      reg_fence<40>(acc);
      release2(B_BEMPTY + 2);
      x_chkL(oa[0], xo, par); x_chkL(oa[1], xo + 4 * X_SIZE, par);
      TS(36);
      reg_fence<40>(acc); reg_fence_u<64>(oa[0]);
      wg_fence();
#pragma unroll
      for (int i = 0; i < PKA; i++) wg_rs<80, 1>(acc, &oa[0][4 * i], dw + wo_off(i >> 1) + (i & 1) * 32, XRE || i);
      wg_commit();
      TS(60);
      if (WOS) { if (!wf1) mbar_wait(BAR(B_WOFULL + 1), 0); }
      TS(62);
      bb(P.never);
      const uint32_t pk = peek(po);
      wg_fence();
#pragma unroll
      for (int i = PKA; i < 16; i++) wg_rs<80, 1>(acc, &oa[0][4 * i], dw + wo_off(i >> 1) + (i & 1) * 32, i);
      wg_commit();
      uint32_t seen = peeked(pk, par);
      if (PROBE & 1) probe(seen, 0x0f, po, par);
      TB(59);
#pragma unroll
      for (int i = 0; i < 4; i++) x_load<4, 256>(&ol[0][8 * i], xo + i * X_SIZE + 1536);
      x_chkM(ob, xo + 1024, par);
      if (PROBE & 1) probe(seen, 0xf0, po, par);
      wg_wait<0>();
      reg_fence<40>(acc); reg_fence_u<64>(oa[0]); reg_fence_u<32>(ob);
      TS(37);
#pragma unroll
      for (int i = 0; i < 4; i++) x_load<4, 256>(&ol[1][8 * i], xo + (4 + i) * X_SIZE + 1536);
      if (REL == 2) release2(B_BEMPTY);
      if (REL == 1 || REL == 2) release2(B_BEMPTY + 1);
      wg_fence();
#pragma unroll
      for (int i = 0; i < 8; i++) wg_rs<80, 1>(acc, &ob[4 * i], dw + wo_off(i) + 64, 1);
      wg_commit();
#pragma unroll
      for (int b = 0; b < 2; b++) {
        x_chkL(ol[b], xo + 4 * b * X_SIZE + 1536, par);
        TS(38 + b);
        reg_fence<40>(acc); reg_fence_u<32>(ol[b]);
        wg_fence();
#pragma unroll
        for (int i = 0; i < 4; i++)
#pragma unroll
          for (int kk = 0; kk < 2; kk++) wg_rs<80, 1>(acc, &ol[b][8 * i + 4 * kk], dw + wo_off(4 * b + i) + (kk + 3) * 32, 1);
        wg_commit();
      }
      TS(56);
      if (!BFL) mbar_wait(BAR(B_BFULL), 0);
      TS(57);
      wg_wait<0>();
      reg_fence<40>(acc); reg_fence_u<32>(ob); reg_fence_u<64>(ol[0]);
      if (WOS == 2) reg_fence_u<32>(oa[1]);
      if (RL3 < 0) release2(B_BEMPTY + 3);
      if (RL4 < 0) release2(B_BEMPTY + 4);
      if (RL5 < 0) release2(B_BEMPTY + 5);
      TS(6);
      uint8_t* const gh = xo + (c * X_SIZE + X_H);
#pragma unroll
      for (int j = 0; j < 10; j++) {
        const uint32_t h0 = pack2(acc[4 * j], acc[4 * j + 1]);
        hbits = __funnelshift_r(hbits, h0, 1);
        fa[2 * j] = tag(h0, par);
        fa[2 * j + 1] = pack2(acc[4 * j + 2], acc[4 * j + 3]);
        stx(gh + j * 256, fa[2 * j], fa[2 * j + 1]);
      }
      TS(7);
    }
    pad<PAD4>(P.never);
    const bool lag = TAILR ? w : (wr ^ c) & 1;
    float acc5[80];
    uint32_t pk5, seen5;
    const uint8_t* pga;
    const uint8_t* const xg = xo + (X_G + u * (7168 - 2560));
    auto gsrc = [&](int n) {
      const int e = G_ORDER >> (4 * (n - 8)), i = e & 3;
      return xg + (i == 0 ? c : (((i - 1) + (i - 1 >= (c >> 1))) << 1) + (c & 1)) * X_SIZE + ((e >> 2) & 1) * 3584;
    };
    auto pg = [&]() { const int l = lane_again(); return gsrc(8 + (l & 7)) - l * 8 + 13 * 256; };
    {
      float acc[112];
      reg_def<112>(acc);
      const uint8_t* const xh = xo + X_H;
      uint32_t seen = 0, st[8];
      float mean0, mean1, hr0, hr1, off[4 * NOFF];
      uint32_t csa2;
      const uint8_t* const xs = xo + (int)(X_S - u * (2560 - 128) - g * 16 - t * 8 + 2 * t * X_SIZE);
      auto ph = [&]() { const int l = lane_again(); return xh - l * 8 + peer((l + 1) & 7) * X_SIZE + 9 * 256; };
#pragma unroll
      for (int n = 0; n < 8; n++) {
        const int b = n & 3, s = n % 6;
        const uint64_t db = mkdesc(sb + b_slot(s), 2560, 512, 2);
        if (BFL && n == 0) mbar_wait(BAR(B_BFULL), 0);
        if (n) {
          mbar_wait(BAR(B_BFULL + s), (n / 6) & 1);
          x_chk10(f[b], xh + peer(n) * X_SIZE, par);
        }
        if (n && 2 * n == RL3) release2(B_BEMPTY + 3);
        if (n && 2 * n == RL4) release2(B_BEMPTY + 4);
        if (n && 2 * n == RL5) release2(B_BEMPTY + 5);
        if (n == 1) TS(8);
        TB(40 + n);
        if (n == 1) {
          if (PROBE & 32) probe(seen, 6, ph(), par);
          x_load<10, 256>(f[2], xh + peer(2) * X_SIZE); x_load<10, 256>(f[3], xh + peer(3) * X_SIZE);
        }
        if (LAG) {
          if (!lag && n == LAG + LAG0) asm volatile("bar.arrive 14, 256;" ::: "memory");
          if (lag && n == LAG0) asm volatile("bar.sync 14, 256;" ::: "memory");
        }
        if (LAGE && lag && n == LAGE) asm volatile("bar.sync 10, 256;" ::: "memory");
        if (n) bb(P.never);
        reg_fence<112>(acc); reg_fence_u<20>(f[b]);
        wg_fence();
        {
#pragma unroll
        for (int kk = 0; kk < 5; kk++) wg_rs<224, 1>(acc, f[b] + 4 * kk, db + w1off(kk), kk || n);
        }
        wg_commit();
        if (LAGE && !lag && n == 7) asm volatile("bar.arrive 10, 256;" ::: "memory");
        if (n == 0) {
          TS(19);
          if (PROBE & 2) probe(seen, 1, ph(), par);
          TS(20);
          x_load<10, 256>(f[1], xh + peer(1) * X_SIZE);
          if (RL3 == 1) release2(B_BEMPTY + 3);
          if (RL4 == 1) release2(B_BEMPTY + 4);
          if (RL5 == 1) release2(B_BEMPTY + 5);
          float a0 = 0.f, q0 = 0.f, a1 = 0.f, q1 = 0.f;
#pragma unroll
          for (int j = 0; j < 10; j++) {
            const float b0 = bf_lo(fa[2 * j]), b1 = bf_hi(fa[2 * j]), b2 = bf_lo(fa[2 * j + 1]), b3 = bf_hi(fa[2 * j + 1]);
            a0 += b0 + b1; q0 = fmaf(b0, b0, fmaf(b1, b1, q0)); a1 += b2 + b3; q1 = fmaf(b2, b2, fmaf(b3, b3, q1));
          }
#pragma unroll
          for (int o = 1; o <= 2; o <<= 1) {
            a0 += __shfl_xor_sync(0xffffffffu, a0, o); q0 += __shfl_xor_sync(0xffffffffu, q0, o);
            a1 += __shfl_xor_sync(0xffffffffu, a1, o); q1 += __shfl_xor_sync(0xffffffffu, q1, o);
          }
          stxp(xo + (int)(c * X_SIZE + X_S - u * (2560 - 128) - g * 16), tag(__float_as_uint(t ? a1 : a0), par), __float_as_uint(t ? q1 : q0), t < 2);
          wg_wait<0>();
          release2(B_BEMPTY);
        } else {
          if (EPI == 3 ? n == STN : n == 7 && !EPI) {
            x_chkS(st, xs, par);
            float sa0 = __uint_as_float(st[0]) + __uint_as_float(st[4]), sq0 = __uint_as_float(st[1]) + __uint_as_float(st[5]);
            float sa1 = __uint_as_float(st[2]) + __uint_as_float(st[6]), sq1 = __uint_as_float(st[3]) + __uint_as_float(st[7]);
#pragma unroll
            for (int o = 1; o <= 2; o <<= 1) {
              sa0 += __shfl_xor_sync(0xffffffffu, sa0, o); sq0 += __shfl_xor_sync(0xffffffffu, sq0, o);
              sa1 += __shfl_xor_sync(0xffffffffu, sa1, o); sq1 += __shfl_xor_sync(0xffffffffu, sq1, o);
            }
            mean0 = sa0 * (1.f / DM); mean1 = sa1 * (1.f / DM);
            hr0 = 0.5f * rsq_a(fmaxf(sq0 * (1.f / DM) - mean0 * mean0, 0.f) + 1e-5f);
            hr1 = 0.5f * rsq_a(fmaxf(sq1 * (1.f / DM) - mean1 * mean1, 0.f) + 1e-5f);
            if (EPI) { mean0 *= -hr0; mean1 *= -hr1; }
            asm volatile("" : "+f"(mean0), "+f"(mean1), "+f"(hr0), "+f"(hr1));
            if (EPI) { float a[4] = {mean0, mean1, hr0, hr1}; bbp4(P.never, a); mean0 = a[0]; mean1 = a[1]; hr0 = a[2]; hr1 = a[3]; }
            mbar_wait(BAR(B_CS + 1), 0);
          }
          if (!(EPI == 1 && n == 7)) {
            wg_wait<1>();
            reg_fence_u<20>(f[(b + 3) & 3]); reg_fence_u<20>(f[(b + 2) & 3]);
            if (n > 1) release2(B_BEMPTY + (n - 1) % 6);
          }
          if (EPI == 3 && n == OFN) {
            csa2 = sb + SM_CS2 + 8 * (lane_again() & 3);
#pragma unroll
            for (int j = 0; j < NOFF; j++) {
              const float2 cs = lds64f(csa2 + j * 32);
              off[4 * j] = mean0 * cs.x; off[4 * j + 1] = mean0 * cs.y; off[4 * j + 2] = mean1 * cs.x; off[4 * j + 3] = mean1 * cs.y;
            }
            if constexpr (NOFF == 12) bbf48(P.never, off);
            if constexpr (NOFF == 8) bbf32(P.never, off);
          }
          if (n == (EPI ? STN - 1 : 6)) { x_load<2, 8>(st, xs); x_load<2, 8>(st + 4, xs + X_SIZE); }
        }
        if (n == 2 || n == 4) {
          if (PROBE & 4) probe(seen, 3 << (n + 1), ph(), par);
          x_load<10, 256>(f[b ^ 2], xh + peer(n + 2) * X_SIZE); x_load<10, 256>(f[(b ^ 2) + 1], xh + peer(n + 3) * X_SIZE);
        }
      }
      bool w8, w9;
      wg_wait<0>();
      reg_fence<112>(acc); reg_fence_u<20>(f[3]);
      TS(9); PL(5);
      uint8_t* const gg = xo + (c * X_SIZE + X_G + u * (7168 - 2560));
#pragma unroll
      for (int j = 0; j < 28; j++) {
        uint32_t* const gf = j < 14 ? fa + 2 * j : fb + 2 * (j - 14);
        const float2 cs = lds64f(sb + SM_CS2 + (j * 8 + 2 * t) * 4);
        const float y0 = fmaf(-mean0, cs.x, acc[4 * j]) * hr0, y1 = fmaf(-mean0, cs.y, acc[4 * j + 1]) * hr0;
        const float y2 = fmaf(-mean1, cs.x, acc[4 * j + 2]) * hr1, y3 = fmaf(-mean1, cs.y, acc[4 * j + 3]) * hr1;
        gf[0] = tag(pack2(fmaf(y0, tanh_a(y0), y0), fmaf(y1, tanh_a(y1), y1)), par);
        gf[1] = pack2(fmaf(y2, tanh_a(y2), y2), fmaf(y3, tanh_a(y3), y3));
        if (j < 14 || !DEFER5) stx(gg + j * 256, gf[0], gf[1]);
        if (j == 13) {
          release2(B_BEMPTY + 1);
          pad<PADE>(P.never);
          w8 = mbar_test(BAR(B_BFULL + 2), 1); w9 = mbar_test(BAR(B_BFULL + 3), 1);
          TB(49);
          PL(7);
        }
        if (j == PEEK5) pk5 = peek(pg());
        if (j == 13) {
          if (!w8) mbar_wait(BAR(B_BFULL + 2), 1);
          TB(48);
          reg_def<80>(acc5);
          reg_fence_u<28>(f[0]);
        }
        if (j >= 13 && (j & 1)) {
          if (j > 13) bb4(P.never, gf - 2);
          if (j < 27) {
            wg_fence();
            wg_rs<160, 1>(acc5, f[0] + 2 * (j - 13), mkdesc(sb + b_slot(2), 3584, 512, 2) + w2off((j - 13) / 2), j - 13);
            if (j == 25) wg_commit();
          }
        }
      }
      TS(10); PL(8);
      if (STEP5 == 5) {
        seen5 = peeked(pk5, par);
        if (PROBE & 8) probe(seen5, 28, pg(), par);
        TS(23);
        x_load<14, 256>(f[2], gsrc(10)); x_load<14, 256>(f[3], gsrc(11));
        if (DEFER5) {
#pragma unroll
          for (int j = 0; j < 14; j++) stx(const_cast<uint8_t*>(gsrc(9)) + j * 256, fb[2 * j], fb[2 * j + 1]);
        }
      }
      seen5 = peeked(pk5, par);
      if (PROBE & 8) probe(seen5, NEED5, EPI ? pga : pg(), par);
      TS(23);
      if (!w9) mbar_wait(BAR(B_BFULL + 3), 1);
      x_load<14, 256>(f[2], gsrc(10)); x_load<14, 256>(f[3], gsrc(11));
      reg_fence_u<28>(f[1]);
      wg_fence();
#pragma unroll
      for (int kk = 0; kk < (BAL5 ? 5 : 7); kk++) {
        if (BAL5 && kk == BP9 - 6 && c < 6) {
          wg_rs<160, 1>(acc5, f[1] + 20, mkdesc(sb + b_slot(3), 3584, 512, 2) + w2off(5), 1);
          wg_rs<160, 1>(acc5, f[1] + 24, mkdesc(sb + b_slot(3), 3584, 512, 2) + w2off(6), 1);
        }
        wg_rs<160, 1>(acc5, f[1] + 4 * kk, mkdesc(sb + b_slot(3), 3584, 512, 2) + w2off(kk), 1);
      }
      wg_commit();
      if (TAIL5) { wg_wait<1>(); if (!RA5) release2(B_BEMPTY + 2); }
      if (DEFER5 == 1) {
        if (!TAIL5) bb(P.never);
#pragma unroll
        for (int j = 0; j < 14; j++) stx(const_cast<uint8_t*>(gsrc(9)) + j * 256, fb[2 * j], fb[2 * j + 1]);
      }
      if (TAIL5) { wg_wait<0>(); if (!RB5) release2(B_BEMPTY + 3); }
    }
    {
      float* const acc = acc5;
      uint32_t hr[10][2];
      float hf[40];
      uint32_t seen = seen5;
      TS(21);
#pragma unroll
      for (int n = 10; n < 16; n++) {
        const int b = n & 3, s = n % 6;
        const uint64_t db = mkdesc(sb + b_slot(s), 3584, 512, 2);
        mbar_wait(BAR(B_BFULL + s), (n / 6) & 1);
        x_chk14(f[b], gsrc(n), par);
        if (n == 10) TS(11);
        TB(40 + n);
        wg_wait<1>();
        reg_fence_u<28>(f[b ^ 2]);
        if (n < 12) release2(B_BEMPTY + n - 8);
        if (n == 11) {
          seen = peeked(pk5, par);
          if (PROBE & 16) probe(seen, NEED11, pg(), par);
        }
        if (n == 12 && NEED12) { if (PK12) seen = peeked(pk5, par); probe(seen, NEED12, pg(), par); }
        if (n == 13 && NEED13) { if (PK12 > 1) seen = peeked(pk5, par); probe(seen, NEED13, pg(), par); }
        if (n < 14) x_load<14, 256>(f[b ^ 2], gsrc(n + 2));
        if (n == 10 || (n == 11 && PK12) || (n == 12 && PK12 > 1)) pk5 = peek(pg());
        if (n == HRP) x_load<10, 256>(hr[0], xo + (c * X_SIZE + X_H));
        if (n == 15) {
#pragma unroll
          for (int j = 0; j < 10; j++) {
            const uint32_t h0 = tag(hr[j][0], (hbits >> (22 + j)) & 1);
            hf[4 * j] = bf_lo(h0); hf[4 * j + 1] = bf_hi(h0); hf[4 * j + 2] = bf_lo(hr[j][1]); hf[4 * j + 3] = bf_hi(hr[j][1]);
          }
          reg_fence<40>(hf);
        }
        if (n == LAG5 && lag) asm volatile("bar.sync 9, 256;" ::: "memory");
        bb(P.never);
        reg_fence<80>(acc); reg_fence_u<28>(f[b]);
        wg_fence();
#pragma unroll
        for (int kk = 0; kk < (BAL5 && n == 15 ? 5 : 7); kk++) {
          if (BAL5 && n == 15 && kk == BP15 && c >= 6) { wg_rs<160, 1>(acc, f[b] + 20, db + w2off(5), 1); wg_rs<160, 1>(acc, f[b] + 24, db + w2off(6), 1); }
          wg_rs<160, 1>(acc, f[b] + 4 * kk, db + w2off(kk), 1);
        }
        wg_commit();
        if (n == LEAD5 && !lag) asm volatile("bar.arrive 9, 256;" ::: "memory");
      }
      wg_wait<1>();
      reg_fence_u<28>(f[1]); reg_fence_u<28>(f[2]);
      uint32_t pp[40];
      const uint8_t* const gp = g_p + (size_t)(role ^ (int)lag) * 20480 + v * 5120 + lane * 8;
      if (lag) {
        if (PPW == 2) { uint32_t sn = PKT >= 0 ? peeked(pk5, par) : 0; probe(sn, 1, gp - lane_again() * 8 + 19 * 256, par); }
        if (FEWV == 4) TS(62);
        x_load<20, 256>(pp, gp);
      }
      wg_wait<0>();
      reg_fence<80>(acc); reg_fence_u<28>(f[3]);
      TS(12); PL(13);
      if (c & 1) {
#pragma unroll
        for (int j = 0; j < 40; j++) asm volatile("add.f32 %0, %0, %1;" : "+f"(acc[40 + j]) : "f"(hf[j]));
      } else {
#pragma unroll
        for (int j = 0; j < 40; j++) asm volatile("add.f32 %0, %0, %1;" : "+f"(acc[j]) : "f"(hf[j]));
      }
      if (!lag) {
#pragma unroll
        for (int j = 0; j < 20; j++) {
          reg_fence<4>(acc + 4 * j);
          stx(const_cast<uint8_t*>(gp) + j * 256, tag(pack2(acc[4 * j], acc[4 * j + 1]), par), pack2(acc[4 * j + 2], acc[4 * j + 3]));
        }
      } else {
        uint32_t r[40];
        reg_fence<80>(acc);
#pragma unroll
        for (int j = 0; j < 40; j++) r[j] = pack2(acc[2 * j], acc[2 * j + 1]);
        reg_fence_u<40>(r);
        const int l = lane_again(), row = ((l >> 2) & 1) * 4 + (l >> 3);
        const uint32_t st = sb + SM_OUT + v * 5376;
        uint32_t sta = st + (l & 15) * 336 + (l >> 4) * 16, lda = st + row * 336 + (l & 3) * 16;
        uint8_t* op = P.outp + (size_t)(128 * rb + 64 * (~c & 1) + 16 * v + row) * (2 * DM) + 320 * (c >> 1) + (l & 3) * 16;
        asm volatile("" : "+r"(sta), "+r"(lda), "+l"(op));
        x_chk20(pp, gp, bbv(P.never, par));
        TS(22);
#pragma unroll
        for (int j = 0; j < 40; j++) asm("add.rn.bf16x2 %0, %0, %1;" : "+r"(r[j]) : "r"(pp[j]));
#pragma unroll
        for (int i = 0; i < 20; i += 2) stsm4(sta + i * 16, r[2 * i], r[2 * i + 1], r[2 * i + 2], r[2 * i + 3]);
        __syncwarp();
        uint4 y[10];
#pragma unroll
        for (int i = 0; i < 10; i++) y[i] = lds128(lda + (i / 5) * 8 * 336 + (i % 5) * 64);
#pragma unroll
        for (int i = 0; i < 10; i++)
          asm volatile("st.global.v4.u32 [%0], {%1,%2,%3,%4};" ::"l"(op + (i / 5) * 8 * 2 * DM + (i % 5) * 64), "r"(y[i].x), "r"(y[i].y), "r"(y[i].z), "r"(y[i].w) : "memory");
      }
      pad<PADH>(P.never);
      TS(13);
      TSEND();
    }
  }
}

typedef CUresult (*EncFn)(CUtensorMap*, CUtensorMapDataType, cuuint32_t, void*, const cuuint64_t*, const cuuint64_t*, const cuuint32_t*,
                          const cuuint32_t*, CUtensorMapInterleave, CUtensorMapSwizzle, CUtensorMapL2promotion, CUtensorMapFloatOOBfill);
static void mk_map(EncFn enc, CUtensorMap* m, const void* p, int rank, uint64_t d0, uint64_t d1, uint64_t d2, uint64_t s1, uint64_t s2,
                   uint32_t b0, uint32_t b1, uint32_t b2, CUtensorMapSwizzle sw) {
  cuuint64_t gd[3] = {d0, d1, d2}, gs[2] = {s1, s2};
  cuuint32_t bd[3] = {b0, b1, b2}, es[3] = {1, 1, 1};
  enc(m, CU_TENSOR_MAP_DATA_TYPE_BFLOAT16, rank, const_cast<void*>(p), gd, gs, bd, es, CU_TENSOR_MAP_INTERLEAVE_NONE, sw,
      CU_TENSOR_MAP_L2_PROMOTION_L2_128B, CU_TENSOR_MAP_FLOAT_OOB_FILL_NONE);
}

extern "C" void kernel_launch(void* const* d_in, const int* in_sizes, int n_in, void* d_out, int out_size) {
  static EncFn enc = nullptr;
  static int use_smid = 0;
  cudaLaunchConfig_t cfg = {};
  cudaLaunchAttribute at[1];
  at[0].id = cudaLaunchAttributeClusterDimension; at[0].val.clusterDim.x = 2; at[0].val.clusterDim.y = 1; at[0].val.clusterDim.z = 1;
  cfg.gridDim = dim3(NCTA); cfg.blockDim = dim3(384); cfg.dynamicSmemBytes = SM_TOTAL; cfg.stream = cudaStreamPerThread;
  cfg.attrs = at; cfg.numAttrs = 1;
  if (!enc) {
    void* fn = nullptr; cudaDriverEntryPointQueryResult q;
    cudaGetDriverEntryPoint("cuTensorMapEncodeTiled", &fn, cudaEnableDefault, &q);
    enc = (EncFn)fn;
    cudaFuncSetAttribute(fused_kernel, cudaFuncAttributeMaxDynamicSharedMemorySize, SM_TOTAL);
    int sms = 0, ncl = 0;
    cudaDeviceGetAttribute(&sms, cudaDevAttrMultiProcessorCount, 0);
    cudaOccupancyMaxActiveClusters(&ncl, fused_kernel, &cfg);
    use_smid = (sms == NCTA && ncl == NCTA / 2);
  }
  const CUtensorMapSwizzle S32 = CU_TENSOR_MAP_SWIZZLE_32B, S128 = CU_TENSOR_MAP_SWIZZLE_128B;
  Params P;
  mk_map(enc, &P.x, d_in[0], 2, DM, SEQ, 1, DM * 2, 0, 64, 128, 1, S128);
  mk_map(enc, &P.qkv128, d_in[1], 3, DM, DM, 3, 3 * DM * 2, DM * 2, 64, 32, 3, S128);
  mk_map(enc, &P.qkv32, d_in[1], 3, DM, DM, 3, 3 * DM * 2, DM * 2, 16, 32, 3, S32);
  mk_map(enc, &P.wo, d_in[2], 3, 16, DM, 40, DM * 2, 32, 16, 80, 5, S32);
  mk_map(enc, &P.w1, d_in[4], 3, 32, DM, 54, FF * 2, 64, 32, 40, 7, CU_TENSOR_MAP_SWIZZLE_64B);
  mk_map(enc, &P.w2, d_in[5], 3, 32, FF, 20, DM * 2, 64, 32, 56, 5, CU_TENSOR_MAP_SWIZZLE_64B);
  mk_map(enc, &P.xr, d_in[0], 2, DM, SEQ, 1, DM * 2, 0, 80, 128, 1, CU_TENSOR_MAP_SWIZZLE_NONE);
  mk_map(enc, &P.o, d_out, 2, DM, SEQ, 1, DM * 2, 0, 80, 16, 1, CU_TENSOR_MAP_SWIZZLE_NONE);
  P.xp = (const __nv_bfloat16*)d_in[0]; P.wqkvp = (const __nv_bfloat16*)d_in[1]; P.wop = (const __nv_bfloat16*)d_in[2]; P.w1p = (const __nv_bfloat16*)d_in[4]; P.w2p = (const __nv_bfloat16*)d_in[5];
  P.outp = (uint8_t*)d_out;
  P.use_smid = use_smid; P.never = 0;
  cudaLaunchKernelEx(&cfg, fused_kernel, P);
}
```
